```python
import torch

def _softmax(x, axis=-1):
    return torch.softmax(x, dim=axis)
def _gelu(x):
    return torch.nn.functional.gelu(x, approximate="tanh")
def _silu(x):
    return torch.nn.functional.silu(x)
def _sigmoid(x):
    return torch.sigmoid(x)
def _layernorm(x, axis=-1, eps=1e-5):
    m = x.mean(dim=axis, keepdim=True)
    v = x.var(dim=axis, keepdim=True, unbiased=False)
    return (x - m) / torch.sqrt(v + eps)
def _scatter_add(tgt, idx, src, axis=0):
    return tgt.clone().index_add_(axis, idx, src)
def _segment_sum(src, seg, n):
    out = torch.zeros((n,) + src.shape[1:], dtype=src.dtype)
    return out.index_add_(0, seg, src)
def _pad(x, pw):
    flat = tuple(v for pair in reversed(pw) for v in pair)
    return torch.nn.functional.pad(x, flat)

kernel_name = 'recurrent_scan__sliding_block_cached__glu_gated_swiglu__decode'

def setup_inputs():

    _w = (lambda a: (lambda t: t.to(torch.bfloat16) if t.is_floating_point() else t)(torch.as_tensor(a)))
    def _A_setup():
        B, Sq, D = 1, 1, 640
        Hq, Hkv, Sk, Dh = 32, 32, 32768, 192
        assert Hq % Hkv == 0, (Hq, Hkv)
        return {
            "x": _w((lambda *s: torch.randn(*s, dtype=torch.bfloat16) * 0.05)(B, Sq, D)),
            "k_cache": _w((lambda *s: torch.randn(*s, dtype=torch.bfloat16) * 3.2)(B, Hkv, Sk, Dh)),
            "v_cache": _w((lambda *s: torch.randn(*s, dtype=torch.bfloat16) * 3.2)(B, Hkv, Sk, Dh)),
            "wq": _w((lambda *s: torch.randn(*s, dtype=torch.bfloat16) * 3.2)(D, Hq * Dh) * (D ** -0.5)),
            "wo": _w((lambda *s: torch.randn(*s, dtype=torch.bfloat16) * 3.2)(Hq * Dh, D) * ((Hq * Dh) ** -0.5)),
        }
    _A_in = _A_setup()

    def _B_setup():
        B, S, D, F = 1, 1, 640, 1536
        return {
            "x": _w((lambda *s: torch.randn(*s, dtype=torch.bfloat16) * 0.05)(B, S, D)),
            "w1": _w((lambda *s: torch.randn(*s, dtype=torch.bfloat16) * 0.4)(D, F) * (2.0 / D) ** 0.5),
            "w3": _w((lambda *s: torch.randn(*s, dtype=torch.bfloat16) * 0.4)(D, F) * (2.0 / D) ** 0.5),
            "w2": _w((lambda *s: torch.randn(*s, dtype=torch.bfloat16) * 0.4)(F, D) * (2.0 / F) ** 0.5),
        }
    _B_in = _B_setup()

    return {
        "A_x": _A_in["x"],
        "A_k_cache": _A_in["k_cache"],
        "A_v_cache": _A_in["v_cache"],
        "A_wq": _A_in["wq"],
        "A_wo": _A_in["wo"],
        "B_x": _B_in["x"],
        "B_w1": _B_in["w1"],
        "B_w3": _B_in["w3"],
        "B_w2": _B_in["w2"],
    }

def reference(A_x, A_k_cache, A_v_cache, A_wq, A_wo, B_x, B_w1, B_w3, B_w2):
    def _A_ref(x, k_cache, v_cache, wq, wo):
        B, Sq, D = x.shape
        Hq, Dh = 32, 192
        Hkv, Sk = k_cache.shape[1], k_cache.shape[2]
        W = min(4096, max(256, Sk // 4))
        rep = Hq // Hkv
        q = (lambda x, *d: x.permute(*d))((x @ wq).reshape(B, Sq, Hq, Dh), 0, 2, 1, 3)
        k = (lambda x, n, axis: torch.repeat_interleave(x, n, dim=axis))(k_cache[:, :, Sk - W:, :], rep, axis=1)
        v = (lambda x, n, axis: torch.repeat_interleave(x, n, dim=axis))(v_cache[:, :, Sk - W:, :], rep, axis=1)
        scores = torch.einsum("bhqd,bhkd->bhqk", q, k) * (Dh ** -0.5)
        p = _softmax(scores, axis=-1)
        o = torch.einsum("bhqk,bhkd->bhqd", p, v)
        return (lambda x, *d: x.permute(*d))(o, 0, 2, 1, 3).reshape(B, Sq, Hq * Dh) @ wo

    def _B_ref(x, w1, w3, w2):
        gate = torch.einsum("bsd,df->bsf", x, w1)
        up = torch.einsum("bsd,df->bsf", x, w3)
        h = _silu(gate) * up
        out = torch.einsum("bsf,fd->bsd", h, w2)
        return out

    x = A_x
    xn = _layernorm(x, axis=-1)
    s = _A_ref(xn, A_k_cache, A_v_cache, A_wq, A_wo)
    g = _silu(_B_ref(xn, B_w1, B_w3, B_w2))
    return x + s * g
```

```cpp
#include <cuda_runtime.h>
#include <cuda_bf16.h>
#include <cuda.h>
#include <stdint.h>

namespace {

constexpr int D_MODEL = 640;
constexpr int N_HEAD = 32;
constexpr int D_HEAD = 192;
constexpr int SEQ = 32768;
constexpr int WIN = 4096;
constexpr int D_FF = 1536;

constexpr int SPLIT = 4;
constexpr int N_CTA = N_HEAD * SPLIT;
constexpr int TILE_ROWS = WIN / N_CTA;
constexpr int TILE_BYTES = TILE_ROWS * D_HEAD * 2;
constexpr int N_SLOT = 16;

constexpr int ROWS_PER_CTA = D_MODEL / SPLIT;
constexpr int FF_GROUP = 16;
constexpr int FF_ROWS = D_MODEL / FF_GROUP;
constexpr int FF_PER_CTA = D_FF / N_CTA;
constexpr int Q_PER_CTA = D_HEAD / SPLIT;

constexpr int OWN_COLS = 16;
constexpr int N_OWN = D_MODEL / OWN_COLS;
constexpr int XO_ROWS = 1024;
constexpr int PIECE_ROWS = 64;
constexpr int PIECE_BYTES = PIECE_ROWS * OWN_COLS * 2;
constexpr int W2_PIECES = D_FF / PIECE_ROWS, N_PIECE = W2_PIECES + XO_ROWS / PIECE_ROWS;
constexpr int N_WO = N_CTA / 2;
constexpr int GROUP0 = XO_ROWS / 8;
constexpr int WO_ROUNDS = (N_HEAD * D_HEAD / 8 - GROUP0) / N_WO;
constexpr int WO_BYTES = 8 * D_MODEL * 2;
constexpr int XO_GROUPS = GROUP0 / N_WO;
constexpr int AHEAD_ROWS = 4;
constexpr int AHEAD_FROM = 4, AHEAD_W2 = D_FF / (N_WO * AHEAD_ROWS), AHEAD_END = AHEAD_W2 + XO_ROWS / (N_WO * AHEAD_ROWS);

constexpr int T_W1 = 5, T_W3 = 6;
constexpr int T_K = 8;
constexpr int T_V = T_K + N_HEAD;
constexpr int T_END = T_V + N_HEAD;
constexpr int N_PLAIN = 2;

constexpr int W13_BYTES = FF_ROWS * 192 * 2;
constexpr int TAIL_SLOT = T_END % N_SLOT;
constexpr int WO_WRAP = 9;

constexpr int N_CONS_WARPS = 8;
constexpr int N_CONS = N_CONS_WARPS * 32;
constexpr int N_AUX = 4;
constexpr int N_THREADS = N_CONS + 64 + N_AUX * 32;

constexpr double PACE = 484, PACE_WO = 480, PACE_REF_GBS = 3352.32;
constexpr double PACE_START = 250;
constexpr int PIECE_LAG = 130, AHEAD_LAG = 640, X5_LAG = 1540;
constexpr double PACE_AHEAD = 490;
constexpr int INFLIGHT = 5;
constexpr int SUB_ROWS = 16;
constexpr int MAX_SHIFT = 400;
constexpr int LATE_TILE = 53, LATE_NS = 1160, LATE_GAIN = 9, MAX_LATE = 2000;
constexpr int N_LATE = 8;

constexpr int X1_STRIDE = 576;
constexpr int X2_STRIDE = 8;
constexpr int X3_HEAD = N_CTA * D_HEAD;
constexpr int FIN_STRIDE = 20;
constexpr int V_WARPS = 6;
constexpr int Q_TILE = 12;
constexpr int FFN_TILE = 15;
constexpr int S_DELAY = 12;
constexpr int O_DELAY = 4;
constexpr int O_RACING = 6;
constexpr int O_LAG = 700;
constexpr int XO_TILE = 18;
constexpr int X5_PIECE = 12;
constexpr int LATE_READ = LATE_TILE + 5;

constexpr unsigned SPIN_LIMIT = 1u << 22;

constexpr int SM_RING = 0;
constexpr int SM_H = N_SLOT * TILE_BYTES;
constexpr int SM_BAR = SM_H + (D_FF + XO_ROWS) * 2;
constexpr int SM_XN = SM_BAR + 832;
constexpr int SM_Q = SM_XN + 1280;
constexpr int SM_O = SM_Q + N_HEAD * 384;
constexpr int SM_ML = SM_O + 192;
constexpr int SM_M = SM_ML + 64;
constexpr int SM_S = SM_M + 128;
constexpr int SM_FIN = SM_S + 256;
constexpr int SM_P = SM_FIN + 16 * FIN_STRIDE * 4 + 512;
constexpr int SM_ALLOC = SM_P + 2048 + 1024;
static_assert(SM_ALLOC <= 232448, "shared memory");

__device__ uint32_t g_epoch;
__device__ __align__(128) uint32_t g_x1[N_CTA * X1_STRIDE];
__device__ __align__(128) uint32_t g_xq[N_HEAD * D_HEAD];
__device__ __align__(128) uint32_t g_x2[N_HEAD * N_CTA * X2_STRIDE];
__device__ __align__(128) uint32_t g_xs[N_HEAD * X2_STRIDE];
__device__ __align__(128) uint32_t g_x3[N_HEAD * X3_HEAD];
__device__ __align__(128) uint32_t g_xh[D_FF];
__device__ __align__(128) uint32_t g_xt[N_CTA];
__device__ __align__(128) uint32_t g_xl[N_CTA];
__device__ __align__(128) uint32_t g_xm[N_LATE * 32];
__device__ __align__(128) uint32_t g_xo[XO_ROWS];
__device__ __align__(128) uint32_t g_x5[N_OWN * N_WO * OWN_COLS];

__device__ __forceinline__ uint32_t smem_u32(const void* p) { return (uint32_t)__cvta_generic_to_shared(p); }

__device__ __forceinline__ void mbar_init(uint32_t bar, uint32_t cnt) {
    asm volatile("mbarrier.init.shared::cta.b64 [%0], %1;" ::"r"(bar), "r"(cnt) : "memory");
}
__device__ __forceinline__ void mbar_expect_tx(uint32_t bar, uint32_t bytes) {
    asm volatile("mbarrier.arrive.expect_tx.shared::cta.b64 _, [%0], %1;" ::"r"(bar), "r"(bytes) : "memory");
}
__device__ __forceinline__ void mbar_arrive(uint32_t bar) {
    asm volatile("mbarrier.arrive.shared::cta.b64 _, [%0];" ::"r"(bar) : "memory");
}
__device__ __forceinline__ void mbar_wait(uint32_t bar, uint32_t parity) {
    asm volatile(
        "{\n.reg .pred p;\n.reg .u32 n;\n"
        "mov.u32 n, 0;\n"
        "WAIT_LOOP:\n"
        "mbarrier.try_wait.parity.shared::cta.b64 p, [%0], %1;\n"
        "@p bra WAIT_DONE;\n"
        "add.u32 n, n, 1;\n"
        "setp.lt.u32 p, n, %2;\n"
        "@p bra WAIT_LOOP;\n"
        "WAIT_DONE:\n}"
        ::"r"(bar), "r"(parity), "n"(SPIN_LIMIT) : "memory");
}
__device__ __forceinline__ void named_sync(int id, int n) {
    asm volatile("bar.sync %0, %1;" ::"r"(id), "r"(n) : "memory");
}
__device__ __forceinline__ void named_arrive(int id, int n) {
    asm volatile("bar.arrive %0, %1;" ::"r"(id), "r"(n) : "memory");
}
__device__ __forceinline__ bool elect_one() {
    uint32_t pred = 0;
    asm volatile("{ .reg .pred p; elect.sync _|p, 0xffffffff; @p mov.u32 %0, 1; }" : "+r"(pred));
    return pred;
}
__device__ __forceinline__ uint64_t stream_policy() {
    uint64_t pol;
    asm volatile("createpolicy.fractional.L2::evict_first.b64 %0, 1.0;" : "=l"(pol));
    return pol;
}
__device__ __forceinline__ void bulk_load(uint32_t dst, const void* src, uint32_t bytes, uint32_t bar, uint64_t pol) {
    asm volatile("cp.async.bulk.shared::cluster.global.mbarrier::complete_tx::bytes.L2::cache_hint [%0], [%1], %2, [%3], %4;"
                 ::"r"(dst), "l"(src), "r"(bytes), "r"(bar), "l"(pol) : "memory");
}
__device__ __forceinline__ void tma_3d(uint32_t dst, const CUtensorMap* tm, int c0, int c1, int c2, uint32_t bar, uint64_t pol) {
    asm volatile("cp.async.bulk.tensor.3d.shared::cluster.global.mbarrier::complete_tx::bytes.L2::cache_hint [%0], [%1, {%3, %4, %5}], [%2], %6;"
                 ::"r"(dst), "l"(tm), "r"(bar), "r"(c0), "r"(c1), "r"(c2), "l"(pol) : "memory");
}
__device__ __forceinline__ void prefetch_tmap(const CUtensorMap* tm) {
    asm volatile("prefetch.tensormap [%0];" ::"l"(tm) : "memory");
}
__device__ __forceinline__ void ldsm_x4(uint32_t (&r)[4], uint32_t addr) {
    asm volatile("ldmatrix.sync.aligned.m8n8.x4.shared.b16 {%0,%1,%2,%3}, [%4];"
                 : "=r"(r[0]), "=r"(r[1]), "=r"(r[2]), "=r"(r[3]) : "r"(addr) : "memory");
}
__device__ __forceinline__ void ldsm_x4_t(uint32_t (&r)[4], uint32_t addr) {
    asm volatile("ldmatrix.sync.aligned.m8n8.x4.trans.shared.b16 {%0,%1,%2,%3}, [%4];"
                 : "=r"(r[0]), "=r"(r[1]), "=r"(r[2]), "=r"(r[3]) : "r"(addr) : "memory");
}
__device__ __forceinline__ void mma_bf16(float (&c)[4], const uint32_t (&a)[4], uint32_t b0, uint32_t b1) {
    asm volatile("mma.sync.aligned.m16n8k16.row.col.f32.bf16.bf16.f32 {%0,%1,%2,%3}, {%4,%5,%6,%7}, {%8,%9}, {%0,%1,%2,%3};"
                 : "+f"(c[0]), "+f"(c[1]), "+f"(c[2]), "+f"(c[3])
                 : "r"(a[0]), "r"(a[1]), "r"(a[2]), "r"(a[3]), "r"(b0), "r"(b1));
}
__device__ __forceinline__ void mma_bf16_k8(float (&c)[4], uint32_t a0, uint32_t a1, uint32_t b0) {
    asm volatile("mma.sync.aligned.m16n8k8.row.col.f32.bf16.bf16.f32 {%0,%1,%2,%3}, {%4,%5}, {%6}, {%0,%1,%2,%3};"
                 : "+f"(c[0]), "+f"(c[1]), "+f"(c[2]), "+f"(c[3]) : "r"(a0), "r"(a1), "r"(b0));
}
__device__ __forceinline__ void ldsm_x2_t(uint32_t (&r)[2], uint32_t addr) {
    asm volatile("ldmatrix.sync.aligned.m8n8.x2.trans.shared.b16 {%0,%1}, [%2];" : "=r"(r[0]), "=r"(r[1]) : "r"(addr) : "memory");
}
__device__ __forceinline__ float bf16r(float v) {
    uint32_t r;
    asm("cvt.rn.bf16x2.f32 %0, %1, %2;" : "=r"(r) : "f"(v), "f"(0.f));
    return __uint_as_float(r);
}
__device__ __forceinline__ uint32_t lds32(uint32_t addr) {
    uint32_t v;
    asm volatile("ld.shared.b32 %0, [%1];" : "=r"(v) : "r"(addr) : "memory");
    return v;
}
__device__ __forceinline__ float4 lds128(uint32_t addr) {
    float4 v;
    asm volatile("ld.shared.v4.f32 {%0,%1,%2,%3}, [%4];" : "=f"(v.x), "=f"(v.y), "=f"(v.z), "=f"(v.w) : "r"(addr) : "memory");
    return v;
}
__device__ __forceinline__ void sts32(uint32_t addr, float v) {
    asm volatile("st.shared.f32 [%0], %1;" ::"r"(addr), "f"(v) : "memory");
}
__device__ __forceinline__ float bf_lo(uint32_t v) { return __uint_as_float(v << 16); }
__device__ __forceinline__ float bf_hi(uint32_t v) { return __uint_as_float(v & 0xffff0000u); }
__device__ __forceinline__ uint32_t pack_bf16(float lo, float hi) {
    const __nv_bfloat162 p = __floats2bfloat162_rn(lo, hi);
    return *reinterpret_cast<const uint32_t*>(&p);
}
__device__ __forceinline__ uint32_t now_ns() {
    unsigned long long t;
    asm volatile("mov.u64 %0, %%globaltimer;" : "=l"(t));
    return (uint32_t)t;
}

__device__ __forceinline__ void wait_until(uint32_t t_start, uint32_t deadline) {
    unsigned n = 0;
    while (now_ns() - t_start < deadline && ++n < SPIN_LIMIT) {}
}

__device__ __forceinline__ uint32_t ll_pack(float v, uint32_t tag) {
    uint32_t w;
    asm("lop3.b32 %0, %1, 0xfffffffe, %2, 0xEA;" : "=r"(w) : "r"(__float_as_uint(v)), "r"(tag));
    return w;
}
__device__ __forceinline__ float ll_val(uint32_t w) { return __uint_as_float(w); }
__device__ __forceinline__ void ll_check(uint32_t& bad, uint32_t w, uint32_t tag) {
    asm("lop3.b32 %0, %1, %2, %0, 0xBE;" : "+r"(bad) : "r"(w), "r"(tag));
}
__device__ __forceinline__ float ex2(float v) {
    float r;
    asm("ex2.approx.ftz.f32 %0, %1;" : "=f"(r) : "f"(v));
    return r;
}
__device__ __forceinline__ float rcp(float v) {
    float r;
    asm("rcp.approx.ftz.f32 %0, %1;" : "=f"(r) : "f"(v));
    return r;
}
constexpr float LOG2E = 1.4426950408889634f;
__device__ __forceinline__ void ll_store(uint32_t* p, uint32_t w) {
    asm volatile("st.relaxed.gpu.global.b32 [%0], %1;" ::"l"(p), "r"(w) : "memory");
}
__device__ __forceinline__ uint32_t ll_ld(const uint32_t* p) {
    uint32_t v;
    asm volatile("ld.relaxed.gpu.global.b32 %0, [%1];" : "=r"(v) : "l"(p) : "memory");
    return v;
}
__device__ __forceinline__ uint2 ll_ld2(const uint32_t* p) {
    uint2 v;
    asm volatile("ld.relaxed.gpu.global.v2.b32 {%0,%1}, [%2];" : "=r"(v.x), "=r"(v.y) : "l"(p) : "memory");
    return v;
}
__device__ __forceinline__ uint4 ll_ld4(const uint32_t* p) {
    uint4 v;
    asm volatile("ld.relaxed.gpu.global.v4.b32 {%0,%1,%2,%3}, [%4];"
                 : "=r"(v.x), "=r"(v.y), "=r"(v.z), "=r"(v.w) : "l"(p) : "memory");
    return v;
}
template <int N>
__device__ __forceinline__ void ll_poll4(uint4 (&v)[N], const uint32_t* p, int stride, uint32_t tag) {
    unsigned n = 0;
#pragma unroll 1
    while (true) {
        uint32_t bad = 0;
#pragma unroll
        for (int i = 0; i < N; i++) v[i] = ll_ld4(p + i * stride);
#pragma unroll
        for (int i = 0; i < N; i++) { ll_check(bad, v[i].x, tag); ll_check(bad, v[i].y, tag); ll_check(bad, v[i].z, tag); ll_check(bad, v[i].w, tag); }
        if (__all_sync(0xffffffffu, (bad & 1u) == 0) || ++n > SPIN_LIMIT) break;
    }
}
__device__ __forceinline__ uint2 upper_halves(const uint4& v) {
    return make_uint2(__byte_perm(v.x, v.y, 0x7632), __byte_perm(v.z, v.w, 0x7632));
}
template <int N>
__device__ __forceinline__ float ll_poll_sum(const uint32_t* p, int stride, uint32_t tag) {
    uint32_t w[N];
    unsigned n = 0;
#pragma unroll 1
    while (true) {
        uint32_t bad = 0;
#pragma unroll
        for (int i = 0; i < N; i++) w[i] = ll_ld(p + i * stride);
#pragma unroll
        for (int i = 0; i < N; i++) ll_check(bad, w[i], tag);
        if ((bad & 1u) == 0 || ++n > SPIN_LIMIT) break;
    }
    float s = 0.f;
#pragma unroll
    for (int i = 0; i < N; i++) s += ll_val(w[i]);
    return s;
}
__device__ __forceinline__ float pick4(float a, float b, float c, float d, int j) {
    const float lo = (j & 1) ? b : a, hi = (j & 1) ? d : c;
    return (j & 2) ? hi : lo;
}
__device__ __forceinline__ float silu_f(float v) { return v * rcp(1.f + ex2(-LOG2E * v)); }

struct Params {
    const __nv_bfloat16* x;
    const __nv_bfloat16* k_win;
    __nv_bfloat16* out;
    uint32_t step, step_ffn, step_wo, step_ahead, step_start;
    uint32_t t_last, t_late;
    const char* w2;
    const char* wo;
};

__global__ void __launch_bounds__(N_THREADS, 1)
fused_decode_kernel(const Params prm,
                    const __grid_constant__ CUtensorMap tm_wq, const __grid_constant__ CUtensorMap tm_w1,
                    const __grid_constant__ CUtensorMap tm_w3, const __grid_constant__ CUtensorMap tm_k,
                    const __grid_constant__ CUtensorMap tm_v, const __grid_constant__ CUtensorMap tm_wo,
                    const __grid_constant__ CUtensorMap tm_w2, const __grid_constant__ CUtensorMap tm_wc) {
    extern __shared__ uint8_t smem_raw[];
    const uint32_t sb = (smem_u32(smem_raw) + 1023u) & ~1023u;
    uint8_t* sp = smem_raw + (sb - smem_u32(smem_raw));
    const uint32_t bar_full = sb + SM_BAR;
    const uint32_t bar_empty = bar_full + N_SLOT * 8;
    const uint32_t bar_t = bar_empty + N_SLOT * 8;
    const uint32_t go_k = bar_t + 12 * 8, go_s = go_k + 8, go_q = go_k + 16;
    const uint32_t go_b = go_k + 4 * 8;
    const uint32_t bar_s = go_b + 4 * 8;
    const uint32_t go_o = bar_s + 4 * 8;
    const uint32_t bar_q = go_o + 12 * 8;

    const int tid = threadIdx.x;
    const int cta = blockIdx.x;
    volatile uint32_t* t_first = reinterpret_cast<volatile uint32_t*>(sp + SM_BAR + 824);
    const __nv_bfloat16* k0 = prm.k_win + (uint64_t)blockIdx.x * (TILE_ROWS * D_HEAD);
    asm volatile("{ .reg .pred p; .reg .b64 a; setp.lt.u32 p, %1, %2; mad.wide.u32 a, %1, 32, %0; @p prefetch.global.L2 [a]; }"
                 ::"l"(k0), "r"(tid), "n"(TILE_BYTES / 32) : "memory");
    if (tid == N_CONS) {
        const uint32_t t_now = now_ns();
#pragma unroll
        for (int i = 0; i < N_PLAIN; i++) mbar_init(bar_full + (T_K + i) * 8, 1);
        asm volatile("fence.mbarrier_init.release.cluster;" ::: "memory");
        const uint64_t pol = stream_policy();
#pragma unroll
        for (int i = 0; i < N_PLAIN; i++) {
            mbar_expect_tx(bar_full + (T_K + i) * 8, TILE_BYTES);
            bulk_load(sb + SM_RING + (T_K + i) * TILE_BYTES, k0 + (size_t)i * SEQ * D_HEAD, TILE_BYTES, bar_full + (T_K + i) * 8, pol);
        }
        t_first[-1] = 0;
        prefetch_tmap(&tm_wq);
        *t_first = t_now;
#pragma unroll
        for (int i = 0; i < N_SLOT; i++)
            if (i < T_K || i >= T_K + N_PLAIN) mbar_init(bar_full + i * 8, 1);
        asm volatile("fence.mbarrier_init.release.cluster;" ::: "memory");
    }
    const int warp = __shfl_sync(0xffffffffu, tid >> 5, 0), lane = tid & 31;
    const int head = cta / SPLIT, r = cta % SPLIT;
    const int idx = cta >> 1, quad = (idx >> 2) - 2;
    const bool odd = cta & 1;
    const bool owner = !odd && quad >= 0 && quad % 3 != 2;
    const int own = (quad - quad / 3) * 4 + (idx & 3);

    int producer = warp == N_CONS_WARPS;
    asm volatile("" : "+r"(producer));
    if (producer) {
        __syncwarp();
        named_arrive(6, N_THREADS);
        if (elect_one()) {
            const uint64_t pol = stream_policy();
            const uint32_t t_start0 = *t_first;
            uint32_t t_start = t_start0;
            prefetch_tmap(&tm_w1); prefetch_tmap(&tm_w3); prefetch_tmap(&tm_k); prefetch_tmap(&tm_v); prefetch_tmap(&tm_wo);
            prefetch_tmap(&tm_w2); prefetch_tmap(&tm_wc);
            uint32_t deadline = 0;
            bool first = true;
#pragma unroll 1
            for (int t = 0; t <= T_W3; t++) {
                const bool q = t < T_W1;
                const CUtensorMap* tm = q ? &tm_wq : (t == T_W1 ? &tm_w1 : &tm_w3);
                const int c1 = (q ? head : cta / FF_GROUP) * 3;
                const int c2 = q ? r * ROWS_PER_CTA + t * TILE_ROWS : (cta % FF_GROUP) * FF_ROWS;
                const uint32_t dst = sb + SM_RING + (t == T_W3 ? T_W1 * TILE_BYTES + W13_BYTES : t * TILE_BYTES);
                const int rows = q ? SUB_ROWS : 8, pieces = q ? TILE_ROWS / SUB_ROWS : FF_ROWS / 8;
                mbar_expect_tx(bar_full + t * 8, q ? TILE_BYTES : W13_BYTES);
#pragma unroll 1
                for (int j = 0; j < pieces; j++) {
                    wait_until(t_start, deadline);
                    tma_3d(dst + j * rows * 384, tm, 0, c1, c2 + j * rows, bar_full + t * 8, pol);
                    deadline += q ? prm.step : prm.step_ffn;
                    if (first) { deadline += prm.step_start; first = false; }
                }
            }
            mbar_wait(bar_full + 7 * 8, 0);
            mbar_expect_tx(bar_full + (T_K + N_PLAIN) * 8, TILE_BYTES);
#pragma unroll 1
            for (int t = T_K + N_PLAIN; t < T_END; t++) {
                const int slot = t & (N_SLOT - 1), next = (t + 1) & (N_SLOT - 1);
                const uint32_t fb = bar_full + slot * 8, dst = sb + SM_RING + slot * TILE_BYTES;
                const CUtensorMap* tm = t >= T_V ? &tm_v : &tm_k;
                const int row = ((t - T_K) & (N_HEAD - 1)) * SEQ + (SEQ - WIN) + cta * TILE_ROWS;
                wait_until(t_start, deadline);
                tma_3d(dst, tm, 0, 0, row, fb, pol);
                deadline += prm.step;
                mbar_wait(bar_empty + next * 8, (((t + 1) >> 4) - 1) & 1);
                if (t + 1 < T_END) mbar_expect_tx(bar_full + next * 8, TILE_BYTES);
                wait_until(t_start, deadline);
                tma_3d(dst + SUB_ROWS * 384, tm, 0, 0, row + SUB_ROWS, fb, pol);
                deadline += prm.step;
                t_start = t_start0 - t_first[-1];
                const int u = max(t + 1 - INFLIGHT, 7);
                mbar_wait(bar_full + (u & (N_SLOT - 1)) * 8, (u >> 4) & 1);
            }
            if (odd) {
                constexpr int AHEAD_BYTES = AHEAD_ROWS * D_MODEL * 2;
                const char* w2 = prm.w2 + idx * AHEAD_BYTES;
                const char* wo = prm.wo + (idx - AHEAD_W2 * N_WO) * AHEAD_BYTES;
                mbar_wait(bar_empty + (N_SLOT - 1) * 8, 1);
#pragma unroll 1
                for (int n = 0; n < WO_ROUNDS; n++) {
                    const uint32_t dst = n < WO_WRAP ? TAIL_SLOT * TILE_BYTES + n * WO_BYTES : (n - WO_WRAP) * WO_BYTES;
                    wait_until(t_start, deadline);
                    tma_3d(sb + SM_RING + dst, &tm_wo, 0, (GROUP0 + n * N_WO + idx) * 8, 0, bar_t + n * 8, pol);
                    deadline += prm.step_wo;
                    if (n == WO_WRAP - 2) mbar_wait(bar_empty, 0);
                }
                deadline += AHEAD_LAG - prm.step_wo;
#pragma unroll 1
                for (int k = AHEAD_FROM; k < AHEAD_END; k++) {
                    wait_until(t_start, deadline);
                    asm volatile("cp.async.bulk.prefetch.L2.global [%0], %1;"
                                 ::"l"((k < AHEAD_W2 ? w2 : wo) + k * (N_WO * AHEAD_BYTES)), "n"(AHEAD_BYTES) : "memory");
                    deadline += prm.step_ahead;
                }
            }
            if (owner) {
#pragma unroll 1
                for (int k = 0; k < N_HEAD; k++) mbar_expect_tx(bar_q + k * 8, PIECE_BYTES);
                mbar_wait(bar_empty + (TAIL_SLOT + (N_PIECE * PIECE_BYTES - 1) / TILE_BYTES) * 8, 1);
                wait_until(t_start, prm.t_last + PIECE_LAG);
#pragma unroll 1
                for (int k = 0; k < N_PIECE; k++)
                    tma_3d(sb + SM_RING + TAIL_SLOT * TILE_BYTES + k * PIECE_BYTES, k < W2_PIECES ? &tm_w2 : &tm_wc, own * OWN_COLS,
                           (k < W2_PIECES ? k : k - W2_PIECES) * PIECE_ROWS, 0, k < N_HEAD ? bar_q + k * 8 : bar_t + (k - N_HEAD) * 8, pol);
            }
        }
        return;
    }

    if (tid == (N_CONS_WARPS + 1) * 32) {
#pragma unroll 1
        for (int i = 0; i < N_SLOT; i++) mbar_init(bar_empty + i * 8, V_WARPS);
        asm volatile("fence.mbarrier_init.release.cluster;" ::: "memory");
    }
    if (warp >= N_CONS_WARPS + 2 && warp < N_CONS_WARPS + 2 + N_AUX && lane == 0) {
        const uint32_t b0 = bar_t + (warp - (N_CONS_WARPS + 2)) * 17 * 8;
#pragma unroll 1
        for (int i = 0; i < 17; i++) mbar_init(b0 + i * 8, 1);
        asm volatile("fence.mbarrier_init.release.cluster;" ::: "memory");
        if (warp == N_CONS_WARPS + 2) {
#pragma unroll 1
            for (int k = 0; k < WO_ROUNDS; k++) mbar_expect_tx(bar_t + k * 8, odd ? WO_BYTES : PIECE_BYTES);
        }
    }
    __syncwarp();
    uint2 xin = make_uint2(0u, 0u);
    if (warp < 5) xin = *reinterpret_cast<const uint2*>(prm.x + tid * 4);
    volatile uint32_t* s_epoch = reinterpret_cast<volatile uint32_t*>(sp + SM_ML + 60);
    if (tid == 5 * 32) *s_epoch = ll_ld(&g_epoch);

    if (warp == N_CONS_WARPS + 1) {
        const int lc = lane & (OWN_COLS - 1);
        const int col = own * OWN_COLS + lc;
        uint32_t x_lo = 0;
        if (owner) x_lo = reinterpret_cast<const uint16_t*>(prm.x)[col];
        uint16_t* outp = reinterpret_cast<uint16_t*>(prm.out) + col;
        asm volatile("" : "+l"(outp));
        named_sync(6, N_THREADS);
        const uint32_t tag = (*s_epoch + 1u) & 1u;
        if (lane == 0) {
            ll_store(g_xt + cta, (*t_first & ~1u) | tag);
            mbar_arrive(bar_full + 7 * 8);
        }
        {
            const int c = lane < 24 ? lane >> 1 : 0;
            const uint32_t* xf = g_x1 + (cta / FF_GROUP) * FF_GROUP * X1_STRIDE + 192 + (lane & 1) * 192 +
                                 (cta % FF_GROUP) * FF_PER_CTA + c;
            mbar_wait(bar_full + FFN_TILE * 8, 0);
            const float mine = bf16r(ll_poll_sum<16>(xf, X1_STRIDE, tag));
            const float other = __shfl_xor_sync(0xffffffffu, mine, 1);
            const float hv = bf16r(bf16r(silu_f(mine)) * other);
            if (lane < 24 && !(lane & 1)) ll_store(g_xh + cta * FF_PER_CTA + c, __float_as_uint(hv) | tag);
        }
#pragma unroll 1
        for (int b = 0; b < 4; b++) {
            mbar_wait(go_b + b * 8, 0);
            const int h = b * 8 + (lane & 7);
            uint2 v;
            unsigned n = 0;
#pragma unroll 1
            while (true) {
                uint32_t bad = 0;
                v = ll_ld2(g_xs + h * X2_STRIDE);
                ll_check(bad, v.x, tag); ll_check(bad, v.y, tag);
                if (__all_sync(0xffffffffu, (bad & 1u) == 0) || ++n > SPIN_LIMIT) break;
            }
            if (lane < 8) *reinterpret_cast<float2*>(sp + SM_S + h * 8) = make_float2(bf_hi(v.x), ll_val(v.y));
            __syncwarp();
            if (lane == 0) mbar_arrive(bar_s + b * 8);
            if (b == 2) {
                uint32_t due = t_first[0] - t_first[-1] + prm.t_late;
                int late = 0;
#pragma unroll 1
                for (int t = LATE_TILE; t < LATE_TILE + 4; t++) {
                    mbar_wait(bar_full + (t & (N_SLOT - 1)) * 8, (t >> 4) & 1);
                    late += (int)(now_ns() - due);
                    due += 2 * prm.step;
                }
                if (lane == 0) ll_store(g_xl + cta, ((uint32_t)late & ~1u) | tag);
                if (!odd && idx < N_LATE) {
                    mbar_wait(bar_full + (LATE_READ & (N_SLOT - 1)) * 8, (LATE_READ >> 4) & 1);
                    uint4 w[1];
                    ll_poll4<1>(w, g_xl + lane * 4, 0, tag);
                    late = __reduce_add_sync(0xffffffffu, (int)(w[0].x + w[0].y + w[0].z + w[0].w)) / (4 * N_CTA);
                    late = min(max(late * LATE_GAIN / 8, 0), MAX_LATE);
                    if (lane < 8) ll_store(g_xm + idx * 32 + lane, ((uint32_t)late & ~1u) | tag);
                }
            }
        }
        {
            const uint32_t w = ll_ld(g_xm + (idx % N_LATE) * 32);
            if (lane == 0 && ((w ^ tag) & 1u) == 0) t_first[-1] = t_first[-1] - w;
        }
        if (owner) {
            uint32_t fin = sb + SM_FIN + lc * (FIN_STRIDE * 4);
            asm volatile("" : "+r"(fin));
            named_sync(5, N_CONS + 32);
            float fp[8];
#pragma unroll
            for (int i = 0; i < 8; i++) fp[i] = __uint_as_float(lds32(sb + SM_FIN + FIN_STRIDE * 64 + lc * 4 + i * 64));
            const float f = ((fp[0] + fp[1]) + (fp[2] + fp[3])) + ((fp[4] + fp[5]) + (fp[6] + fp[7]));
            const uint32_t g_lo = pack_bf16(silu_f(bf16r(f)), 0.f);
            sts32(fin + 72, __uint_as_float(g_lo));
            named_sync(14, N_AUX * 32 + 32);
            const float4 c = lds128(fin + 32), d = lds128(fin + 48);
            const float gathered = ((c.x + c.y) + (c.z + c.w)) + ((d.x + d.y) + (d.z + d.w));
            sts32(fin + 64, gathered);
            named_sync(12, N_CONS + 32);
            const float4 a = lds128(fin), b = lds128(fin + 16);
            const float sum = (((a.x + gathered) + a.y) + (a.z + a.w)) + ((b.x + b.y) + (b.z + b.w));
            uint32_t res;
            asm("{ .reg .b32 t; mul.rn.bf16x2 t, %1, %2; add.rn.bf16x2 %0, %3, t; }"
                : "=r"(res) : "r"(pack_bf16(sum, 0.f)), "r"(g_lo), "r"(x_lo));
            if (lane < OWN_COLS) asm volatile("st.global.u16 [%0], %1;" ::"l"(outp), "h"((uint16_t)res) : "memory");
        }
        return;
    }
    if (warp >= N_CONS_WARPS + 2) {
        const int fw = warp - (N_CONS_WARPS + 2);
        named_sync(6, N_THREADS);
        const uint32_t epoch = *s_epoch, tag = (epoch + 1u) & 1u;
        mbar_wait(go_q, 0);
        if (fw == N_AUX - 1) {
            const uint4 v = ll_ld4(g_xt + lane * 4);
            uint32_t bad = 0;
            ll_check(bad, v.x, tag); ll_check(bad, v.y, tag); ll_check(bad, v.z, tag); ll_check(bad, v.w, tag);
            const uint32_t t0 = *t_first;
            int d = max(max((int)(t0 - v.x), (int)(t0 - v.y)), max((int)(t0 - v.z), (int)(t0 - v.w)));
#pragma unroll
            for (int o = 16; o > 0; o >>= 1) d = max(d, __shfl_xor_sync(0xffffffffu, d, o));
            if (__all_sync(0xffffffffu, (bad & 1u) == 0) && lane == 0) t_first[-1] = min(max(d, 0), MAX_SHIFT);
        }
        mbar_wait(bar_full + Q_TILE * 8, 0);
#pragma unroll 1
        for (int h = fw; h < N_HEAD; h += N_AUX) {
            uint4 v[2];
            ll_poll4<2>(v, g_xq + h * D_HEAD + (lane % 24) * 4, 96, tag);
            if (lane < 24) {
                *reinterpret_cast<uint2*>(sp + SM_Q + h * 384 + lane * 8) = upper_halves(v[0]);
                *reinterpret_cast<uint2*>(sp + SM_Q + h * 384 + 192 + lane * 8) = upper_halves(v[1]);
            }
            __syncwarp();
            if (lane == 0) mbar_arrive(bar_q + h * 8);
        }
        if (r == 0 && fw == N_AUX - 1) {
            mbar_wait(go_s, 0);
            const uint32_t* xm = g_x2 + (head * N_CTA + lane) * X2_STRIDE;
            uint2 ml[4];
            unsigned n = 0;
#pragma unroll 1
            while (true) {
                uint32_t bad = 0;
#pragma unroll
                for (int i = 0; i < 4; i++) ml[i] = ll_ld2(xm + i * 32 * X2_STRIDE);
#pragma unroll
                for (int i = 0; i < 4; i++) { ll_check(bad, ml[i].x, tag); ll_check(bad, ml[i].y, tag); }
                if (__all_sync(0xffffffffu, (bad & 1u) == 0) || ++n > SPIN_LIMIT) break;
            }
            float m = fmaxf(fmaxf(bf_hi(ml[0].x), bf_hi(ml[1].x)), fmaxf(bf_hi(ml[2].x), bf_hi(ml[3].x)));
#pragma unroll
            for (int o = 16; o > 0; o >>= 1) m = fmaxf(m, __shfl_xor_sync(0xffffffffu, m, o));
            float den = 0.f;
#pragma unroll
            for (int i = 0; i < 4; i++) den = fmaf(ex2((bf_hi(ml[i].x) - m) * LOG2E), ll_val(ml[i].y), den);
#pragma unroll
            for (int o = 16; o > 0; o >>= 1) den += __shfl_xor_sync(0xffffffffu, den, o);
            if (lane < X2_STRIDE) ll_store(g_xs + head * X2_STRIDE + lane, ll_pack(lane == 0 ? m : rcp(den), tag));
            if (cta == 0 && lane == 0) ll_store(&g_epoch, epoch + 1u);
        }
        if (owner) {
            mbar_wait(go_k, 0);
            uint4 v[3];
            ll_poll4<3>(v, g_xh + fw * 384 + lane * 4, 128, tag);
#pragma unroll
            for (int i = 0; i < 3; i++) *reinterpret_cast<uint2*>(sp + SM_H + (fw * 384 + i * 128 + lane * 4) * 2) = upper_halves(v[i]);
        }
#pragma unroll 1
        for (int s = fw; s < (odd ? WO_ROUNDS : XO_GROUPS); s += N_AUX) {
            const int grp = (odd ? GROUP0 : 0) + s * N_WO + idx;
            mbar_wait(go_o + s * 8, 0);
            if (grp >= (N_HEAD - 1) * 24) {
                const uint32_t c0 = clock();
                while ((uint32_t)clock() - c0 < (uint32_t)O_LAG) {}
            }
            uint4 v[8];
            ll_poll4<8>(v, g_x3 + grp * (N_CTA * 8) + lane * 4, 128, tag);
            float t0 = 0.f, t1 = 0.f, t2 = 0.f, t3 = 0.f;
#pragma unroll
            for (int i = 0; i < 8; i += 2) {
                t0 += ll_val(v[i].x) + ll_val(v[i + 1].x); t1 += ll_val(v[i].y) + ll_val(v[i + 1].y);
                t2 += ll_val(v[i].z) + ll_val(v[i + 1].z); t3 += ll_val(v[i].w) + ll_val(v[i + 1].w);
            }
            const bool u2 = lane & 2, u4 = lane & 4;
            const float a = (u2 ? t2 : t0) + __shfl_xor_sync(0xffffffffu, u2 ? t0 : t2, 2);
            const float b = (u2 ? t3 : t1) + __shfl_xor_sync(0xffffffffu, u2 ? t1 : t3, 2);
            float c = (u4 ? b : a) + __shfl_xor_sync(0xffffffffu, u4 ? a : b, 4);
            c += __shfl_xor_sync(0xffffffffu, c, 8);
            c += __shfl_xor_sync(0xffffffffu, c, 16);
            const int e = 4 * (lane & 1) + (lane & 2) + (lane >> 2);
            if (lane < 8) {
                if (odd) reinterpret_cast<uint16_t*>(sp + SM_O)[s * 8 + e] = (uint16_t)pack_bf16(c, 0.f);
                else ll_store(g_xo + grp * 8 + e, __float_as_uint(bf16r(c)) | tag);
            }
            if (s == fw + N_AUX) named_arrive(3, N_CONS + N_AUX * 32);
        }
        if (odd) named_arrive(13, N_CONS + N_AUX * 32);
        if (owner) {
            mbar_wait(go_o + XO_GROUPS * 8, 0);
            uint4 o[2];
            ll_poll4<2>(o, g_xo + fw * 128 + lane * 4, 512, tag);
#pragma unroll
            for (int i = 0; i < 2; i++)
                *reinterpret_cast<uint2*>(sp + SM_H + (D_FF + i * 512 + fw * 128 + lane * 4) * 2) = upper_halves(o[i]);
            named_arrive(4, N_AUX * 32 + N_CONS);
            const uint32_t* p = g_x5 + (own * N_WO + fw * (N_WO / N_AUX)) * OWN_COLS + lane;
            uint32_t dst = sb + SM_FIN + ((lane & 15) * FIN_STRIDE + 8 + fw * 2 + (lane >> 4)) * 4;
            uint32_t t_x5 = prm.t_last + X5_LAG;
            asm volatile("" : "+r"(dst), "+l"(p), "+r"(t_x5));
            mbar_wait(bar_q + X5_PIECE * 8, 1);
            wait_until(t_first[0] - t_first[-1], t_x5);
            unsigned n = 0;
#pragma unroll 1
            while (true) {
                uint32_t w[8];
#pragma unroll
                for (int i = 0; i < 8; i++) w[i] = ll_ld(p + i * 32);
                uint32_t bad[4];
#pragma unroll
                for (int i = 0; i < 4; i++)
                    asm("lop3.b32 %0, %1, %2, %3, 0x7E;" : "=r"(bad[i]) : "r"(w[2 * i]), "r"(w[2 * i + 1]), "r"(tag));
                const float c = ((ll_val(w[0]) + ll_val(w[1])) + (ll_val(w[2]) + ll_val(w[3]))) +
                                ((ll_val(w[4]) + ll_val(w[5])) + (ll_val(w[6]) + ll_val(w[7])));
                sts32(dst, c);
                if (__all_sync(0xffffffffu, !(((bad[0] | bad[1]) | (bad[2] | bad[3])) & 1u)) || ++n > SPIN_LIMIT) break;
            }
            named_arrive(14, N_AUX * 32 + 32);
        }
        return;
    }

    float* sml = reinterpret_cast<float*>(sp + SM_ML);
    if (warp < 5) {
        const uint2 u = xin;
        float s1 = (bf_lo(u.x) + bf_hi(u.x)) + (bf_lo(u.y) + bf_hi(u.y));
#pragma unroll
        for (int o = 16; o > 0; o >>= 1) s1 += __shfl_xor_sync(0xffffffffu, s1, o);
        if (lane == 0) sml[warp] = s1;
        named_sync(10, 160);
        const float mean = (((sml[0] + sml[1]) + (sml[2] + sml[3])) + sml[4]) * (1.f / D_MODEL);
        const float a = bf_lo(u.x) - mean, b = bf_hi(u.x) - mean, c = bf_lo(u.y) - mean, d = bf_hi(u.y) - mean;
        float s2 = fmaf(a, a, fmaf(b, b, fmaf(c, c, d * d)));
#pragma unroll
        for (int o = 16; o > 0; o >>= 1) s2 += __shfl_xor_sync(0xffffffffu, s2, o);
        if (lane == 0) sml[8 + warp] = s2;
        named_sync(10, 160);
        const float var = (((sml[8] + sml[9]) + (sml[10] + sml[11])) + sml[12]) * (1.f / D_MODEL);
        const float mean_b = bf16r(mean);
        float den;
        asm("sqrt.approx.f32 %0, %1;" : "=f"(den) : "f"(bf16r(bf16r(var) + 1e-5f)));
        const float inv = rcp(bf16r(den));
        const uint32_t d0 = pack_bf16(bf_lo(u.x) - mean_b, bf_hi(u.x) - mean_b);
        const uint32_t d1 = pack_bf16(bf_lo(u.y) - mean_b, bf_hi(u.y) - mean_b);
        *reinterpret_cast<uint2*>(sp + SM_XN + tid * 8) =
            make_uint2(pack_bf16(bf_lo(d0) * inv, bf_hi(d0) * inv), pack_bf16(bf_lo(d1) * inv, bf_hi(d1) * inv));
    }
    named_sync(6, N_THREADS);
    const uint32_t tag = (*s_epoch + 1u) & 1u;
    if (tid < Q_PER_CTA) ll_store(g_xq + cta * Q_PER_CTA + tid, tag ^ 1u);

    const int q4 = lane & 3, g8 = lane >> 2;
    const int rowT = (lane & 7) + ((lane >> 4) << 3), hiT = (lane >> 3) & 1;

    uint32_t* x1 = g_x1 + cta * X1_STRIDE + q4 * 8 + g8;
    if (warp < 6) {
        const uint32_t xn_addr = sb + SM_XN + (r * ROWS_PER_CTA + 2 * q4) * 2;
        const int line = 3 * rowT + (warp >> 1);
        const uint32_t o0 = (line * 128 + ((hiT ^ (line & 7)) << 4)) ^ ((warp & 1) << 6), o1 = o0 ^ 32;
        float acc[2][4] = {};
#pragma unroll 1
        for (int t = 0; t < 5; t++) {
            mbar_wait(bar_full + t * 8, 0);
            const uint32_t tb = sb + SM_RING + t * TILE_BYTES;
#pragma unroll
            for (int kk = 0; kk < 2; kk++) {
                const uint32_t b0 = lds32(xn_addr + (t * 32 + kk * 16) * 2);
                const uint32_t b1 = lds32(xn_addr + (t * 32 + kk * 16 + 8) * 2);
                uint32_t a[4];
                ldsm_x4_t(a, tb + kk * 6144 + o0);
                mma_bf16(acc[0], a, b0, b1);
                ldsm_x4_t(a, tb + kk * 6144 + o1);
                mma_bf16(acc[1], a, b0, b1);
            }
        }
        ll_store(x1 + warp * 32, ll_pack(pick4(acc[0][0], acc[0][2], acc[1][0], acc[1][2], q4), tag));
        mbar_wait(bar_full + T_W3 * 8, 0);
        named_sync(11, 192);
        if (tid < 5 * V_WARPS) mbar_arrive(bar_empty + (tid / V_WARPS) * 8);
        if (tid < Q_PER_CTA) {
            const float qv = ll_poll_sum<4>(g_x1 + head * SPLIT * X1_STRIDE + r * Q_PER_CTA + tid, X1_STRIDE, tag);
            ll_store(g_xq + cta * Q_PER_CTA + tid, __float_as_uint(bf16r(qv)) | tag);
        }
        __syncwarp();
        if (tid == 0) mbar_arrive(go_q);
    } else {
        float acc[12][4] = {};
        mbar_wait(bar_full + (T_W1 + warp - 6) * 8, 0);
        const uint32_t xf_addr = sb + SM_XN + ((cta % FF_GROUP) * FF_ROWS + 2 * q4) * 2;
        uint32_t ad[3];
#pragma unroll
        for (int j = 0; j < 3; j++)
            ad[j] = sb + SM_RING + T_W1 * TILE_BYTES + (warp - 6) * W13_BYTES + (3 * rowT + j) * 128 + ((hiT ^ ((3 * rowT + j) & 7)) << 4);
#pragma unroll 1
        for (int ks = 0; ks < 3; ks++) {
            const uint32_t b0 = lds32(xf_addr + ks * 32);
            uint32_t b1 = 0u, step = ks * 6144;
            if (ks < 2) b1 = lds32(xf_addr + ks * 32 + 16);
            else if (lane >= 16) step -= 8 * 384;
#pragma unroll
            for (int mt = 0; mt < 12; mt++) {
                uint32_t a[4];
                ldsm_x4_t(a, (ad[mt >> 2] + step) ^ ((mt & 3) << 5));
                mma_bf16(acc[mt], a, b0, b1);
            }
        }
#pragma unroll
        for (int i = 0; i < 6; i++)
            ll_store(x1 + 192 + (warp - 6) * 192 + i * 32,
                     ll_pack(pick4(acc[2 * i][0], acc[2 * i][2], acc[2 * i + 1][0], acc[2 * i + 1][2], q4), tag));
        named_sync(7, 64);
        if (tid >= 192 && tid < 192 + 3 * V_WARPS) mbar_arrive(bar_empty + (T_W1 + (tid - 192) / V_WARPS) * 8);
    }
    named_sync(1, N_CONS);

    {
        const int rowN = (lane & 7) + (((lane >> 3) & 1) << 3), hiN = lane >> 4;
#pragma unroll 1
        for (int h = warp; h < N_HEAD; h += N_CONS_WARPS) {
            const int t = T_K + h, slot = t & (N_SLOT - 1);
            mbar_wait(bar_q + h * 8, 0);
            mbar_wait(bar_full + slot * 8, (t >> 4) & 1);
            const uint32_t tb = sb + SM_RING + slot * TILE_BYTES;
            const int swz = h < N_PLAIN ? 0 : 7;
            float acc[2][2][4] = {};
#pragma unroll 1
            for (int j = 0; j < 3; j++) {
                const uint32_t oj = tb + (3 * rowN + j) * 128 + ((hiN ^ ((3 * rowN + j) & swz)) << 4);
                const uint32_t qa = sb + SM_Q + h * 384 + (j * 64 + 2 * q4) * 2;
#pragma unroll
                for (int k = 0; k < 4; k++) {
                    const uint32_t b0 = lds32(qa + k * 32), b1 = lds32(qa + k * 32 + 16);
                    uint32_t a[4];
                    ldsm_x4(a, oj ^ (k << 5));
                    mma_bf16(acc[0][k & 1], a, b0, b1);
                    ldsm_x4(a, (oj + 6144) ^ (k << 5));
                    mma_bf16(acc[1][k & 1], a, b0, b1);
                }
            }
            __syncwarp();
            if (lane < V_WARPS) mbar_arrive(bar_empty + slot * 8);
            const float raw = pick4(acc[0][0][0] + acc[0][1][0], acc[0][0][2] + acc[0][1][2],
                                    acc[1][0][0] + acc[1][1][0], acc[1][0][2] + acc[1][1][2], q4);
            const float sc = bf16r(bf16r(raw) * 0.07216878364870323f);
            float mw = sc;
#pragma unroll
            for (int o = 16; o > 0; o >>= 1) mw = fmaxf(mw, __shfl_xor_sync(0xffffffffu, mw, o));
            const float p = ex2((sc - mw) * LOG2E);
            reinterpret_cast<uint16_t*>(sp + SM_P)[h * 32 + q4 * 8 + g8] = (uint16_t)pack_bf16(p, 0.f);
            float lw = p;
#pragma unroll
            for (int o = 16; o > 0; o >>= 1) lw += __shfl_xor_sync(0xffffffffu, lw, o);
            if (lane < X2_STRIDE) ll_store(g_x2 + (h * N_CTA + cta) * X2_STRIDE + lane, ll_pack(lane == 0 ? mw : lw, tag));
            if (lane == 0) {
                reinterpret_cast<float*>(sp + SM_M)[h] = mw;
                if (h == head + S_DELAY) mbar_arrive(go_s);
                if (h >= 23 && (h & 7) == 7) mbar_arrive(go_b + ((h >> 3) - 2) * 8);
            }
        }
    }
    if (odd && q4 < 2) {
#pragma unroll
        for (int j = 0; j < 5; j++) ll_store(g_x5 + ((j * 8 + warp) * N_WO + idx) * OWN_COLS + q4 * 8 + g8, tag ^ 1u);
    }
    named_sync(1, N_CONS);
    if (tid == 0) mbar_arrive(go_k);

    if (warp < V_WARPS) {
        const int line = 3 * rowT + (warp >> 1);
        const uint32_t o0 = (line * 128 + ((hiT ^ (line & 7)) << 4)) ^ ((warp & 1) << 6), o1 = o0 ^ 32;
        uint32_t* x3 = g_x3 + ((warp * 4 + q4) * N_CTA + cta) * 8 + g8;
#pragma unroll
        for (int h = N_HEAD - O_RACING; h < N_HEAD; h++) ll_store(x3 + h * X3_HEAD, tag ^ 1u);
        int s_next = 0, h_next = ((odd ? GROUP0 : 0) + idx) / 24 + O_DELAY;
#pragma unroll 1
        for (int h = 0; h < N_HEAD; h++) {
            const int slot = (T_V + h) & (N_SLOT - 1);
            if ((h & 7) == 0) mbar_wait(bar_s + h, 0);
            const float2 ms = *reinterpret_cast<const float2*>(sp + SM_S + h * 8);
            const float scale = ex2((reinterpret_cast<const float*>(sp + SM_M)[h] - ms.x) * LOG2E) * ms.y;
            mbar_wait(bar_full + slot * 8, ((T_V + h) >> 4) & 1);
            const uint32_t tb = sb + SM_RING + slot * TILE_BYTES;
            const uint32_t pa = sb + SM_P + (h * 32 + 2 * q4) * 2;
            float oacc[2][2][4] = {};
#pragma unroll
            for (int kk = 0; kk < 2; kk++) {
                const uint32_t b0 = lds32(pa + kk * 32), b1 = lds32(pa + kk * 32 + 16);
                uint32_t a[4];
                ldsm_x4_t(a, tb + kk * 6144 + o0);
                mma_bf16(oacc[0][kk], a, b0, b1);
                ldsm_x4_t(a, tb + kk * 6144 + o1);
                mma_bf16(oacc[1][kk], a, b0, b1);
            }
            __syncwarp();
            if (lane == 0) mbar_arrive(bar_empty + slot * 8);
            const float v = pick4(oacc[0][0][0] + oacc[0][1][0], oacc[0][0][2] + oacc[0][1][2],
                                  oacc[1][0][0] + oacc[1][1][0], oacc[1][0][2] + oacc[1][1][2], q4);
            ll_store(x3 + h * X3_HEAD, ll_pack(v * scale, tag));
            if (tid == 0) {
                if (h == head + S_DELAY - N_HEAD) mbar_arrive(go_s);
                if (h == 10 || h == 21) mbar_arrive(go_b + (h == 10 ? 2 : 3) * 8);
                while (h == h_next) {
                    mbar_arrive(go_o + s_next * 8);
                    s_next++;
                    if (odd) h_next = s_next < WO_ROUNDS ? min((GROUP0 + s_next * N_WO + idx) / 24 + O_DELAY, N_HEAD - 1) : -1;
                    else h_next = s_next < XO_GROUPS ? (s_next * N_WO + idx) / 24 + O_DELAY : s_next == XO_GROUPS ? XO_TILE : -1;
                }
            }
        }
    }

    constexpr int STEPS = N_PIECE / N_CONS_WARPS, W2_STEPS = W2_PIECES / N_CONS_WARPS;
    uint32_t hb[STEPS][4][2];
    if (owner) {
        named_sync(4, N_AUX * 32 + N_CONS);
#pragma unroll
        for (int k = 0; k < STEPS; k++)
#pragma unroll
            for (int i = 0; i < 4; i++) {
                const uint32_t ha = sb + SM_H + ((k * N_CONS_WARPS + warp) * PIECE_ROWS + i * 16 + 2 * q4) * 2;
                hb[k][i][0] = lds32(ha);
                hb[k][i][1] = lds32(ha + 16);
            }
    }

    if (odd) {
        uint32_t* x5 = g_x5 + (warp * N_WO + idx) * OWN_COLS + (q4 & 1) * 8 + g8;
        asm volatile("" : "+l"(x5));
        named_sync(3, N_CONS + N_AUX * 32);
        float acc[5][4] = {};
        uint32_t wa = sb + SM_RING + TAIL_SLOT * TILE_BYTES + (lane >> 4) * 2048 + (warp >> 2) * 1024 + (lane & 7) * 128 +
                      (((((warp & 3) << 1) | hiT) ^ (lane & 7)) << 4);
        auto multiply = [&](int p) {
            const uint32_t b0 = lds32(sb + SM_O + (p * 8 + 2 * q4) * 2);
            mbar_wait(bar_t + p * 8, 0);
            uint32_t a0[4], a1[4], a2[2];
            ldsm_x4_t(a0, wa);
            ldsm_x4_t(a1, wa + 4096);
            ldsm_x2_t(a2, wa + 8192);
            mma_bf16_k8(acc[0], a0[0], a0[1], b0);
            mma_bf16_k8(acc[1], a0[2], a0[3], b0);
            mma_bf16_k8(acc[2], a1[0], a1[1], b0);
            mma_bf16_k8(acc[3], a1[2], a1[3], b0);
            mma_bf16_k8(acc[4], a2[0], a2[1], b0);
        };
#pragma unroll 1
        for (int p = 0; p < WO_ROUNDS - 1; p++) {
            if (p == 2 * N_AUX) named_sync(13, N_CONS + N_AUX * 32);
            multiply(p);
            wa += p == WO_WRAP - 1 ? -(TAIL_SLOT * TILE_BYTES + (WO_WRAP - 1) * WO_BYTES) : WO_BYTES;
        }
        multiply(WO_ROUNDS - 1);
#pragma unroll
        for (int j = 0; j < 5; j++) ll_store(x5 + j * 8 * N_WO * OWN_COLS, ll_pack(q4 & 1 ? acc[j][2] : acc[j][0], tag));
    }

    if (owner) {
        float acc[4][4] = {};
        const uint32_t wa = sb + SM_RING + TAIL_SLOT * TILE_BYTES + (warp * PIECE_ROWS + rowT) * 32 + ((hiT ^ ((lane >> 2) & 1)) << 4);
        uint32_t fin_f = sb + SM_FIN + (16 * FIN_STRIDE + warp * 16 + (q4 & 1) * 8 + g8) * 4;
        uint32_t fin_s = sb + SM_FIN + (((q4 & 1) * 8 + g8) * FIN_STRIDE + warp) * 4;
        uint32_t bar = bar_q + warp * 8;
        asm volatile("" : "+r"(fin_f), "+r"(fin_s), "+r"(bar));
#pragma unroll
        for (int k = 0; k < STEPS; k++) {
            if (k < N_HEAD / N_CONS_WARPS) mbar_wait(bar + k * N_CONS_WARPS * 8, 1);
            else mbar_wait(bar - (bar_q - bar_t), 0);
            uint32_t a[4][4];
#pragma unroll
            for (int i = 0; i < 4; i++) ldsm_x4_t(a[i], wa + k * N_CONS_WARPS * PIECE_BYTES + i * 512);
#pragma unroll
            for (int i = 0; i < 4; i++) mma_bf16(acc[i], a[i], hb[k][i][0], hb[k][i][1]);
            if (k == W2_STEPS - 1 || k == STEPS - 1) {
                const float part = q4 ? (acc[0][2] + acc[1][2]) + (acc[2][2] + acc[3][2]) : (acc[0][0] + acc[1][0]) + (acc[2][0] + acc[3][0]);
                if (q4 < 2) sts32(k < W2_STEPS ? fin_f : fin_s, part);
                named_arrive(k < W2_STEPS ? 5 : 12, N_CONS + 32);
#pragma unroll
                for (int i = 0; i < 4; i++) acc[0][i] = acc[1][i] = acc[2][i] = acc[3][i] = 0.f;
            }
        }
    }
    return;
}


typedef CUresult (*EncodeTiledFn)(CUtensorMap*, CUtensorMapDataType, cuuint32_t, void*, const cuuint64_t*,
                                  const cuuint64_t*, const cuuint32_t*, const cuuint32_t*, CUtensorMapInterleave,
                                  CUtensorMapSwizzle, CUtensorMapL2promotion, CUtensorMapFloatOOBfill);

void encode_map(EncodeTiledFn fn, CUtensorMap* m, const void* base, cuuint64_t d1, cuuint64_t d2, cuuint64_t s1,
                cuuint64_t s2, cuuint32_t b1, cuuint32_t b2) {
    const cuuint64_t dims[3] = {64, d1, d2};
    const cuuint64_t strides[2] = {s1, s2};
    const cuuint32_t box[3] = {64, b1, b2};
    const cuuint32_t estr[3] = {1, 1, 1};
    fn(m, CU_TENSOR_MAP_DATA_TYPE_BFLOAT16, 3, const_cast<void*>(base), dims, strides, box, estr,
       CU_TENSOR_MAP_INTERLEAVE_NONE, CU_TENSOR_MAP_SWIZZLE_128B, CU_TENSOR_MAP_L2_PROMOTION_NONE,
       CU_TENSOR_MAP_FLOAT_OOB_FILL_NONE);
}

}

extern "C" void kernel_launch(void* const* d_in, const int* in_sizes, int n_in, void* d_out, int out_size) {
    (void)in_sizes; (void)n_in; (void)out_size;
    static EncodeTiledFn encode = nullptr;
    static double pace_scale = 1.0;
    if (!encode) {
        int dev = 0, mem_khz = 0, bus_bits = 0;
        cudaGetDevice(&dev);
        cudaDeviceGetAttribute(&mem_khz, cudaDevAttrMemoryClockRate, dev);
        cudaDeviceGetAttribute(&bus_bits, cudaDevAttrGlobalMemoryBusWidth, dev);
        const double peak_gbs = 2.0 * mem_khz * 1e-6 * bus_bits / 8.0;
        if (peak_gbs > 0.0) pace_scale = PACE_REF_GBS / peak_gbs;
        void* fn = nullptr;
        cudaDriverEntryPointQueryResult qr;
        cudaGetDriverEntryPoint("cuTensorMapEncodeTiled", &fn, cudaEnableDefault, &qr);
        encode = reinterpret_cast<EncodeTiledFn>(fn);
        cudaFuncSetAttribute(fused_decode_kernel, cudaFuncAttributeMaxDynamicSharedMemorySize, SM_ALLOC);
    }
    CUtensorMap tm_k, tm_v, tm_wq, tm_w1, tm_w3, tm_wo, tm_w2, tm_wc;
    {
        const cuuint64_t dims[3] = {D_MODEL, D_FF, 1};
        const cuuint64_t strides[2] = {D_MODEL * 2, (cuuint64_t)D_MODEL * 2 * D_FF};
        const cuuint32_t box[3] = {OWN_COLS, PIECE_ROWS, 1};
        const cuuint32_t estr[3] = {1, 1, 1};
        encode(&tm_w2, CU_TENSOR_MAP_DATA_TYPE_BFLOAT16, 3, d_in[8], dims, strides, box, estr, CU_TENSOR_MAP_INTERLEAVE_NONE,
               CU_TENSOR_MAP_SWIZZLE_32B, CU_TENSOR_MAP_L2_PROMOTION_NONE, CU_TENSOR_MAP_FLOAT_OOB_FILL_NONE);
        encode(&tm_wc, CU_TENSOR_MAP_DATA_TYPE_BFLOAT16, 3, d_in[4], dims, strides, box, estr, CU_TENSOR_MAP_INTERLEAVE_NONE,
               CU_TENSOR_MAP_SWIZZLE_32B, CU_TENSOR_MAP_L2_PROMOTION_NONE, CU_TENSOR_MAP_FLOAT_OOB_FILL_NONE);
    }
    encode_map(encode, &tm_k, d_in[1], 3, (cuuint64_t)N_HEAD * SEQ, 128, D_HEAD * 2, 3, SUB_ROWS);
    encode_map(encode, &tm_v, d_in[2], 3, (cuuint64_t)N_HEAD * SEQ, 128, D_HEAD * 2, 3, SUB_ROWS);
    encode_map(encode, &tm_wq, d_in[3], N_HEAD * 3, D_MODEL, 128, N_HEAD * D_HEAD * 2, 3, SUB_ROWS);
    encode_map(encode, &tm_w1, d_in[6], D_FF / 64, D_MODEL, 128, D_FF * 2, 3, 8);
    encode_map(encode, &tm_w3, d_in[7], D_FF / 64, D_MODEL, 128, D_FF * 2, 3, 8);
    encode_map(encode, &tm_wo, d_in[4], N_HEAD * D_HEAD, D_MODEL / 64, D_MODEL * 2, 128, 8, 10);
    Params prm;
    prm.x = static_cast<const __nv_bfloat16*>(d_in[0]);
    prm.k_win = static_cast<const __nv_bfloat16*>(d_in[1]) + (size_t)(SEQ - WIN) * D_HEAD;
    prm.out = static_cast<__nv_bfloat16*>(d_out);
    auto step = [&](double pace, double bytes) { return (uint32_t)(pace * pace_scale * bytes / TILE_BYTES + 0.01); };
    prm.step = step(PACE, SUB_ROWS * 384);
    prm.step_ffn = step(PACE, 8 * 384);
    prm.step_wo = step(PACE_WO, WO_BYTES / 2);
    prm.step_start = (uint32_t)(PACE_START * pace_scale + 0.5);
    prm.step_ahead = step(PACE_AHEAD, AHEAD_ROWS * D_MODEL);
    const uint32_t t_k = prm.step_start + 2 * T_W1 * prm.step + 2 * (FF_ROWS / 8) * prm.step_ffn;
    prm.t_late = t_k + (2 * (LATE_TILE - T_K - N_PLAIN) + 1) * prm.step + LATE_NS;
    prm.t_last = t_k + 2 * (T_END - T_K - N_PLAIN) * prm.step + (WO_ROUNDS - 1) * prm.step_wo;
    prm.w2 = static_cast<const char*>(d_in[8]);
    prm.wo = static_cast<const char*>(d_in[4]);
    fused_decode_kernel<<<N_CTA, N_THREADS, SM_ALLOC, cudaStreamPerThread>>>(
        prm, tm_wq, tm_w1, tm_w3, tm_k, tm_v, tm_wo, tm_w2, tm_wc);
}
```

```cpp
#include <cuda_runtime.h>
#include <cuda_bf16.h>
#include <cuda.h>
#include <stdint.h>

namespace {

constexpr int D_MODEL = 640;
constexpr int N_HEAD = 32;
constexpr int D_HEAD = 192;
constexpr int SEQ = 32768;
constexpr int WIN = 4096;
constexpr int D_FF = 1536;

constexpr int SPLIT = 4;
constexpr int N_CTA = N_HEAD * SPLIT;
constexpr int TILE_ROWS = WIN / N_CTA;
constexpr int TILE_BYTES = TILE_ROWS * D_HEAD * 2;
constexpr int N_SLOT = 16;

constexpr int ROWS_PER_CTA = D_MODEL / SPLIT;
constexpr int FF_GROUP = 16;
constexpr int FF_ROWS = D_MODEL / FF_GROUP;
constexpr int FF_PER_CTA = D_FF / N_CTA;
constexpr int Q_PER_CTA = D_HEAD / SPLIT;

constexpr int OWN_COLS = 16;
constexpr int N_OWN = D_MODEL / OWN_COLS;
constexpr int XO_ROWS = 1024;
constexpr int PIECE_ROWS = 64;
constexpr int PIECE_BYTES = PIECE_ROWS * OWN_COLS * 2;
constexpr int W2_PIECES = D_FF / PIECE_ROWS, N_PIECE = W2_PIECES + XO_ROWS / PIECE_ROWS;
constexpr int N_WO = N_CTA / 2;
constexpr int GROUP0 = XO_ROWS / 8;
constexpr int WO_ROUNDS = (N_HEAD * D_HEAD / 8 - GROUP0) / N_WO;
constexpr int WO_BYTES = 8 * D_MODEL * 2;
constexpr int XO_GROUPS = GROUP0 / N_WO;
constexpr int AHEAD_ROWS = 4;
constexpr int AHEAD_FROM = 4, AHEAD_W2 = D_FF / (N_WO * AHEAD_ROWS), AHEAD_END = AHEAD_W2 + XO_ROWS / (N_WO * AHEAD_ROWS);

constexpr int T_W1 = 5, T_W3 = 6;
constexpr int T_K = 8;
constexpr int T_V = T_K + N_HEAD;
constexpr int T_END = T_V + N_HEAD;
constexpr int N_PLAIN = 2;

constexpr int W13_BYTES = FF_ROWS * 192 * 2;
constexpr int TAIL_SLOT = T_END % N_SLOT;
constexpr int WO_WRAP = 9;

constexpr int N_CONS_WARPS = 8;
constexpr int N_CONS = N_CONS_WARPS * 32;
constexpr int N_AUX = 4;
constexpr int N_THREADS = N_CONS + 64 + N_AUX * 32;

constexpr double PACE = 484, PACE_WO = 480, PACE_REF_GBS = 3352.32;
constexpr double PACE_START = 250;
constexpr int PIECE_LAG = 130, AHEAD_LAG = 640, X5_LAG = 1540;
constexpr double PACE_AHEAD = 490;
constexpr int INFLIGHT = 5;
constexpr int SUB_ROWS = 16;
constexpr int MAX_SHIFT = 400;
constexpr int LATE_TILE = 53, LATE_NS = 1160, LATE_GAIN = 9, MAX_LATE = 2000;
constexpr int N_LATE = 8;

constexpr int X1_STRIDE = 576;
constexpr int X2_STRIDE = 8;
constexpr int X3_HEAD = N_CTA * D_HEAD;
constexpr int FIN_STRIDE = 20;
constexpr int V_WARPS = 6;
constexpr int Q_TILE = 12;
constexpr int FFN_TILE = 15;
constexpr int S_DELAY = 12;
constexpr int O_DELAY = 4;
constexpr int O_RACING = 6;
constexpr int O_LAG = 700;
constexpr int XO_TILE = 18;
constexpr int X5_PIECE = 12;
constexpr int LATE_READ = LATE_TILE + 5;

constexpr unsigned SPIN_LIMIT = 1u << 22;

constexpr int SM_RING = 0;
constexpr int SM_H = N_SLOT * TILE_BYTES;
constexpr int SM_BAR = SM_H + (D_FF + XO_ROWS) * 2;
constexpr int SM_XN = SM_BAR + 832;
constexpr int SM_Q = SM_XN + 1280;
constexpr int SM_O = SM_Q + N_HEAD * 384;
constexpr int SM_ML = SM_O + 192;
constexpr int SM_M = SM_ML + 64;
constexpr int SM_S = SM_M + 128;
constexpr int SM_FIN = SM_S + 256;
constexpr int SM_P = SM_FIN + 16 * FIN_STRIDE * 4 + 512;
constexpr int SM_ALLOC = SM_P + 2048 + 1024;
static_assert(SM_ALLOC <= 232448, "shared memory");

__device__ uint32_t g_epoch;
__device__ __align__(128) uint32_t g_x1[N_CTA * X1_STRIDE];
__device__ __align__(128) uint32_t g_xq[N_HEAD * D_HEAD];
__device__ __align__(128) uint32_t g_x2[N_HEAD * N_CTA * X2_STRIDE];
__device__ __align__(128) uint32_t g_xs[N_HEAD * X2_STRIDE];
__device__ __align__(128) uint32_t g_x3[N_HEAD * X3_HEAD];
__device__ __align__(128) uint32_t g_xh[D_FF];
__device__ __align__(128) uint32_t g_xt[N_CTA];
__device__ __align__(128) uint32_t g_xl[N_CTA];
__device__ __align__(128) uint32_t g_xm[N_LATE * 32];
__device__ __align__(128) uint32_t g_xo[XO_ROWS];
__device__ __align__(128) uint32_t g_x5[N_OWN * N_WO * OWN_COLS];

__device__ __forceinline__ uint32_t smem_u32(const void* p) { return (uint32_t)__cvta_generic_to_shared(p); }

__device__ __forceinline__ void mbar_init(uint32_t bar, uint32_t cnt) {
    asm volatile("mbarrier.init.shared::cta.b64 [%0], %1;" ::"r"(bar), "r"(cnt) : "memory");
}
__device__ __forceinline__ void mbar_expect_tx(uint32_t bar, uint32_t bytes) {
    asm volatile("mbarrier.arrive.expect_tx.shared::cta.b64 _, [%0], %1;" ::"r"(bar), "r"(bytes) : "memory");
}
__device__ __forceinline__ void mbar_arrive(uint32_t bar) {
    asm volatile("mbarrier.arrive.shared::cta.b64 _, [%0];" ::"r"(bar) : "memory");
}
__device__ __forceinline__ void mbar_wait(uint32_t bar, uint32_t parity) {
    asm volatile(
        "{\n.reg .pred p;\n.reg .u32 n;\n"
        "mov.u32 n, 0;\n"
        "WAIT_LOOP:\n"
        "mbarrier.try_wait.parity.shared::cta.b64 p, [%0], %1;\n"
        "@p bra WAIT_DONE;\n"
        "add.u32 n, n, 1;\n"
        "setp.lt.u32 p, n, %2;\n"
        "@p bra WAIT_LOOP;\n"
        "WAIT_DONE:\n}"
        ::"r"(bar), "r"(parity), "n"(SPIN_LIMIT) : "memory");
}
__device__ __forceinline__ bool mbar_try(uint32_t bar, uint32_t parity) {
    uint32_t ok;
    asm volatile("{ .reg .pred p; mbarrier.try_wait.parity.shared::cta.b64 p, [%1], %2; selp.u32 %0, 1, 0, p; }"
                 : "=r"(ok) : "r"(bar), "r"(parity) : "memory");
    return ok;
}
__device__ __forceinline__ void named_sync(int id, int n) {
    asm volatile("bar.sync %0, %1;" ::"r"(id), "r"(n) : "memory");
}
__device__ __forceinline__ void named_arrive(int id, int n) {
    asm volatile("bar.arrive %0, %1;" ::"r"(id), "r"(n) : "memory");
}
__device__ __forceinline__ bool elect_one() {
    uint32_t pred = 0;
    asm volatile("{ .reg .pred p; elect.sync _|p, 0xffffffff; @p mov.u32 %0, 1; }" : "+r"(pred));
    return pred;
}
__device__ __forceinline__ uint64_t stream_policy() {
    uint64_t pol;
    asm volatile("createpolicy.fractional.L2::evict_first.b64 %0, 1.0;" : "=l"(pol));
    return pol;
}
__device__ __forceinline__ void bulk_load(uint32_t dst, const void* src, uint32_t bytes, uint32_t bar, uint64_t pol) {
    asm volatile("cp.async.bulk.shared::cluster.global.mbarrier::complete_tx::bytes.L2::cache_hint [%0], [%1], %2, [%3], %4;"
                 ::"r"(dst), "l"(src), "r"(bytes), "r"(bar), "l"(pol) : "memory");
}
__device__ __forceinline__ void tma_3d(uint32_t dst, const CUtensorMap* tm, int c0, int c1, int c2, uint32_t bar, uint64_t pol) {
    asm volatile("cp.async.bulk.tensor.3d.shared::cluster.global.mbarrier::complete_tx::bytes.L2::cache_hint [%0], [%1, {%3, %4, %5}], [%2], %6;"
                 ::"r"(dst), "l"(tm), "r"(bar), "r"(c0), "r"(c1), "r"(c2), "l"(pol) : "memory");
}
__device__ __forceinline__ void prefetch_tmap(const CUtensorMap* tm) {
    asm volatile("prefetch.tensormap [%0];" ::"l"(tm) : "memory");
}
__device__ __forceinline__ void ldsm_x4(uint32_t (&r)[4], uint32_t addr) {
    asm volatile("ldmatrix.sync.aligned.m8n8.x4.shared.b16 {%0,%1,%2,%3}, [%4];"
                 : "=r"(r[0]), "=r"(r[1]), "=r"(r[2]), "=r"(r[3]) : "r"(addr) : "memory");
}
__device__ __forceinline__ void ldsm_x4_t(uint32_t (&r)[4], uint32_t addr) {
    asm volatile("ldmatrix.sync.aligned.m8n8.x4.trans.shared.b16 {%0,%1,%2,%3}, [%4];"
                 : "=r"(r[0]), "=r"(r[1]), "=r"(r[2]), "=r"(r[3]) : "r"(addr) : "memory");
}
__device__ __forceinline__ void mma_bf16(float (&c)[4], const uint32_t (&a)[4], uint32_t b0, uint32_t b1) {
    asm volatile("mma.sync.aligned.m16n8k16.row.col.f32.bf16.bf16.f32 {%0,%1,%2,%3}, {%4,%5,%6,%7}, {%8,%9}, {%0,%1,%2,%3};"
                 : "+f"(c[0]), "+f"(c[1]), "+f"(c[2]), "+f"(c[3])
                 : "r"(a[0]), "r"(a[1]), "r"(a[2]), "r"(a[3]), "r"(b0), "r"(b1));
}
__device__ __forceinline__ void mma_bf16_k8(float (&c)[4], uint32_t a0, uint32_t a1, uint32_t b0) {
    asm volatile("mma.sync.aligned.m16n8k8.row.col.f32.bf16.bf16.f32 {%0,%1,%2,%3}, {%4,%5}, {%6}, {%0,%1,%2,%3};"
                 : "+f"(c[0]), "+f"(c[1]), "+f"(c[2]), "+f"(c[3]) : "r"(a0), "r"(a1), "r"(b0));
}
__device__ __forceinline__ void ldsm_x2_t(uint32_t (&r)[2], uint32_t addr) {
    asm volatile("ldmatrix.sync.aligned.m8n8.x2.trans.shared.b16 {%0,%1}, [%2];" : "=r"(r[0]), "=r"(r[1]) : "r"(addr) : "memory");
}
__device__ __forceinline__ float bf16r(float v) {
    uint32_t r;
    asm("cvt.rn.bf16x2.f32 %0, %1, %2;" : "=r"(r) : "f"(v), "f"(0.f));
    return __uint_as_float(r);
}
__device__ __forceinline__ uint32_t lds32(uint32_t addr) {
    uint32_t v;
    asm volatile("ld.shared.b32 %0, [%1];" : "=r"(v) : "r"(addr) : "memory");
    return v;
}
__device__ __forceinline__ float4 lds128(uint32_t addr) {
    float4 v;
    asm volatile("ld.shared.v4.f32 {%0,%1,%2,%3}, [%4];" : "=f"(v.x), "=f"(v.y), "=f"(v.z), "=f"(v.w) : "r"(addr) : "memory");
    return v;
}
__device__ __forceinline__ void sts32(uint32_t addr, float v) {
    asm volatile("st.shared.f32 [%0], %1;" ::"r"(addr), "f"(v) : "memory");
}
__device__ __forceinline__ float bf_lo(uint32_t v) { return __uint_as_float(v << 16); }
__device__ __forceinline__ float bf_hi(uint32_t v) { return __uint_as_float(v & 0xffff0000u); }
__device__ __forceinline__ uint32_t pack_bf16(float lo, float hi) {
    const __nv_bfloat162 p = __floats2bfloat162_rn(lo, hi);
    return *reinterpret_cast<const uint32_t*>(&p);
}
__device__ __forceinline__ uint32_t now_ns() {
    unsigned long long t;
    asm volatile("mov.u64 %0, %%globaltimer;" : "=l"(t));
    return (uint32_t)t;
}

__device__ __forceinline__ void wait_until(uint32_t t_start, uint32_t deadline) {
    unsigned n = 0;
    while (now_ns() - t_start < deadline && ++n < SPIN_LIMIT) {}
}

__device__ __forceinline__ uint32_t ll_pack(float v, uint32_t tag) {
    uint32_t w;
    asm("lop3.b32 %0, %1, 0xfffffffe, %2, 0xEA;" : "=r"(w) : "r"(__float_as_uint(v)), "r"(tag));
    return w;
}
__device__ __forceinline__ float ll_val(uint32_t w) { return __uint_as_float(w); }
__device__ __forceinline__ void ll_check(uint32_t& bad, uint32_t w, uint32_t tag) {
    asm("lop3.b32 %0, %1, %2, %0, 0xBE;" : "+r"(bad) : "r"(w), "r"(tag));
}
__device__ __forceinline__ float ex2(float v) {
    float r;
    asm("ex2.approx.ftz.f32 %0, %1;" : "=f"(r) : "f"(v));
    return r;
}
__device__ __forceinline__ float rcp(float v) {
    float r;
    asm("rcp.approx.ftz.f32 %0, %1;" : "=f"(r) : "f"(v));
    return r;
}
constexpr float LOG2E = 1.4426950408889634f;
__device__ __forceinline__ void ll_store(uint32_t* p, uint32_t w) {
    asm volatile("st.relaxed.gpu.global.b32 [%0], %1;" ::"l"(p), "r"(w) : "memory");
}
__device__ __forceinline__ uint32_t ll_ld(const uint32_t* p) {
    uint32_t v;
    asm volatile("ld.relaxed.gpu.global.b32 %0, [%1];" : "=r"(v) : "l"(p) : "memory");
    return v;
}
__device__ __forceinline__ uint2 ll_ld2(const uint32_t* p) {
    uint2 v;
    asm volatile("ld.relaxed.gpu.global.v2.b32 {%0,%1}, [%2];" : "=r"(v.x), "=r"(v.y) : "l"(p) : "memory");
    return v;
}
__device__ __forceinline__ uint4 ll_ld4(const uint32_t* p) {
    uint4 v;
    asm volatile("ld.relaxed.gpu.global.v4.b32 {%0,%1,%2,%3}, [%4];"
                 : "=r"(v.x), "=r"(v.y), "=r"(v.z), "=r"(v.w) : "l"(p) : "memory");
    return v;
}
template <int N>
__device__ __forceinline__ void ll_poll4(uint4 (&v)[N], const uint32_t* p, int stride, uint32_t tag) {
    unsigned n = 0;
#pragma unroll 1
    while (true) {
        uint32_t bad = 0;
#pragma unroll
        for (int i = 0; i < N; i++) v[i] = ll_ld4(p + i * stride);
#pragma unroll
        for (int i = 0; i < N; i++) { ll_check(bad, v[i].x, tag); ll_check(bad, v[i].y, tag); ll_check(bad, v[i].z, tag); ll_check(bad, v[i].w, tag); }
        if (__all_sync(0xffffffffu, (bad & 1u) == 0) || ++n > SPIN_LIMIT) break;
    }
}
__device__ __forceinline__ uint2 upper_halves(const uint4& v) {
    return make_uint2(__byte_perm(v.x, v.y, 0x7632), __byte_perm(v.z, v.w, 0x7632));
}
template <int N>
__device__ __forceinline__ float ll_poll_sum(const uint32_t* p, int stride, uint32_t tag) {
    uint32_t w[N];
    unsigned n = 0;
#pragma unroll 1
    while (true) {
        uint32_t bad = 0;
#pragma unroll
        for (int i = 0; i < N; i++) w[i] = ll_ld(p + i * stride);
#pragma unroll
        for (int i = 0; i < N; i++) ll_check(bad, w[i], tag);
        if ((bad & 1u) == 0 || ++n > SPIN_LIMIT) break;
    }
    float s = 0.f;
#pragma unroll
    for (int i = 0; i < N; i++) s += ll_val(w[i]);
    return s;
}
__device__ __forceinline__ float pick4(float a, float b, float c, float d, int j) {
    const float lo = (j & 1) ? b : a, hi = (j & 1) ? d : c;
    return (j & 2) ? hi : lo;
}
__device__ __forceinline__ float silu_f(float v) { return v * rcp(1.f + ex2(-LOG2E * v)); }

struct Params {
    const __nv_bfloat16* x;
    const __nv_bfloat16* k_win;
    __nv_bfloat16* out;
    uint32_t step, step_ffn, step_wo, step_ahead, step_start;
    uint32_t t_last, t_late;
    const char* w2;
    const char* wo;
};

__global__ void __launch_bounds__(N_THREADS, 1)
fused_decode_kernel(const Params prm,
                    const __grid_constant__ CUtensorMap tm_wq, const __grid_constant__ CUtensorMap tm_w1,
                    const __grid_constant__ CUtensorMap tm_w3, const __grid_constant__ CUtensorMap tm_k,
                    const __grid_constant__ CUtensorMap tm_v, const __grid_constant__ CUtensorMap tm_wo,
                    const __grid_constant__ CUtensorMap tm_w2, const __grid_constant__ CUtensorMap tm_wc) {
    extern __shared__ uint8_t smem_raw[];
    const uint32_t sb = (smem_u32(smem_raw) + 1023u) & ~1023u;
    uint8_t* sp = smem_raw + (sb - smem_u32(smem_raw));
    const uint32_t bar_full = sb + SM_BAR;
    const uint32_t bar_empty = bar_full + N_SLOT * 8;
    const uint32_t bar_t = bar_empty + N_SLOT * 8;
    const uint32_t go_k = bar_t + 12 * 8, go_s = go_k + 8, go_q = go_k + 16;
    const uint32_t go_b = go_k + 4 * 8;
    const uint32_t bar_s = go_b + 4 * 8;
    const uint32_t go_o = bar_s + 4 * 8;
    const uint32_t bar_q = go_o + 12 * 8;

    const int tid = threadIdx.x;
    const int cta = blockIdx.x;
    volatile uint32_t* t_first = reinterpret_cast<volatile uint32_t*>(sp + SM_BAR + 824);
    const __nv_bfloat16* k0 = prm.k_win + (uint64_t)blockIdx.x * (TILE_ROWS * D_HEAD);
    asm volatile("{ .reg .pred p; .reg .b64 a; setp.lt.u32 p, %1, %2; mad.wide.u32 a, %1, 32, %0; @p prefetch.global.L2 [a]; }"
                 ::"l"(k0), "r"(tid), "n"(TILE_BYTES / 32) : "memory");
    if (tid == N_CONS) {
        const uint32_t t_now = now_ns();
#pragma unroll
        for (int i = 0; i < N_PLAIN; i++) mbar_init(bar_full + (T_K + i) * 8, 1);
        asm volatile("fence.mbarrier_init.release.cluster;" ::: "memory");
        const uint64_t pol = stream_policy();
#pragma unroll
        for (int i = 0; i < N_PLAIN; i++) {
            mbar_expect_tx(bar_full + (T_K + i) * 8, TILE_BYTES);
            bulk_load(sb + SM_RING + (T_K + i) * TILE_BYTES, k0 + (size_t)i * SEQ * D_HEAD, TILE_BYTES, bar_full + (T_K + i) * 8, pol);
        }
        t_first[-1] = 0;
        prefetch_tmap(&tm_wq);
        *t_first = t_now;
#pragma unroll
        for (int i = 0; i < N_SLOT; i++)
            if (i < T_K || i >= T_K + N_PLAIN) mbar_init(bar_full + i * 8, 1);
        asm volatile("fence.mbarrier_init.release.cluster;" ::: "memory");
    }
    const int warp = __shfl_sync(0xffffffffu, tid >> 5, 0), lane = tid & 31;
    const int head = cta / SPLIT, r = cta % SPLIT;
    const int idx = cta >> 1, quad = (idx >> 2) - 2;
    const bool odd = cta & 1;
    const bool owner = !odd && quad >= 0 && quad % 3 != 2;
    const int own = (quad - quad / 3) * 4 + (idx & 3);

    int producer = warp == N_CONS_WARPS;
    asm volatile("" : "+r"(producer));
    if (producer) {
        __syncwarp();
        named_arrive(6, N_THREADS);
        if (elect_one()) {
            const uint64_t pol = stream_policy();
            const uint32_t t_start0 = *t_first;
            uint32_t t_start = t_start0;
            prefetch_tmap(&tm_w1); prefetch_tmap(&tm_w3); prefetch_tmap(&tm_k); prefetch_tmap(&tm_v); prefetch_tmap(&tm_wo);
            prefetch_tmap(&tm_w2); prefetch_tmap(&tm_wc);
            uint32_t deadline = 0;
            bool first = true;
#pragma unroll 1
            for (int t = 0; t <= T_W3; t++) {
                const bool q = t < T_W1;
                const CUtensorMap* tm = q ? &tm_wq : (t == T_W1 ? &tm_w1 : &tm_w3);
                const int c1 = (q ? head : cta / FF_GROUP) * 3;
                const int c2 = q ? r * ROWS_PER_CTA + t * TILE_ROWS : (cta % FF_GROUP) * FF_ROWS;
                const uint32_t dst = sb + SM_RING + (t == T_W3 ? T_W1 * TILE_BYTES + W13_BYTES : t * TILE_BYTES);
                const int rows = q ? SUB_ROWS : 8, pieces = q ? TILE_ROWS / SUB_ROWS : FF_ROWS / 8;
                mbar_expect_tx(bar_full + t * 8, q ? TILE_BYTES : W13_BYTES);
#pragma unroll 1
                for (int j = 0; j < pieces; j++) {
                    wait_until(t_start, deadline);
                    tma_3d(dst + j * rows * 384, tm, 0, c1, c2 + j * rows, bar_full + t * 8, pol);
                    deadline += q ? prm.step : prm.step_ffn;
                    if (first) { deadline += prm.step_start; first = false; }
                }
            }
            mbar_wait(bar_full + 7 * 8, 0);
            mbar_expect_tx(bar_full + (T_K + N_PLAIN) * 8, TILE_BYTES);
#pragma unroll 1
            for (int t = T_K + N_PLAIN; t < T_END; t++) {
                const int slot = t & (N_SLOT - 1), next = (t + 1) & (N_SLOT - 1);
                const uint32_t fb = bar_full + slot * 8, dst = sb + SM_RING + slot * TILE_BYTES;
                const CUtensorMap* tm = t >= T_V ? &tm_v : &tm_k;
                const int row = ((t - T_K) & (N_HEAD - 1)) * SEQ + (SEQ - WIN) + cta * TILE_ROWS;
                wait_until(t_start, deadline);
                tma_3d(dst, tm, 0, 0, row, fb, pol);
                deadline += prm.step;
                mbar_wait(bar_empty + next * 8, (((t + 1) >> 4) - 1) & 1);
                if (t + 1 < T_END) mbar_expect_tx(bar_full + next * 8, TILE_BYTES);
                wait_until(t_start, deadline);
                tma_3d(dst + SUB_ROWS * 384, tm, 0, 0, row + SUB_ROWS, fb, pol);
                deadline += prm.step;
                t_start = t_start0 - t_first[-1];
                const int u = max(t + 1 - INFLIGHT, 7);
                mbar_wait(bar_full + (u & (N_SLOT - 1)) * 8, (u >> 4) & 1);
            }
            if (odd) {
                constexpr int AHEAD_BYTES = AHEAD_ROWS * D_MODEL * 2;
                const char* w2 = prm.w2 + idx * AHEAD_BYTES;
                const char* wo = prm.wo + (idx - AHEAD_W2 * N_WO) * AHEAD_BYTES;
                mbar_wait(bar_empty + (N_SLOT - 1) * 8, 1);
#pragma unroll 1
                for (int n = 0; n < WO_ROUNDS; n++) {
                    const uint32_t dst = n < WO_WRAP ? TAIL_SLOT * TILE_BYTES + n * WO_BYTES : (n - WO_WRAP) * WO_BYTES;
                    wait_until(t_start, deadline);
                    tma_3d(sb + SM_RING + dst, &tm_wo, 0, (GROUP0 + n * N_WO + idx) * 8, 0, bar_t + n * 8, pol);
                    deadline += prm.step_wo;
                    if (n == WO_WRAP - 2) mbar_wait(bar_empty, 0);
                }
                deadline += AHEAD_LAG - prm.step_wo;
#pragma unroll 1
                for (int k = AHEAD_FROM; k < AHEAD_END; k++) {
                    wait_until(t_start, deadline);
                    asm volatile("cp.async.bulk.prefetch.L2.global [%0], %1;"
                                 ::"l"((k < AHEAD_W2 ? w2 : wo) + k * (N_WO * AHEAD_BYTES)), "n"(AHEAD_BYTES) : "memory");
                    deadline += prm.step_ahead;
                }
            }
            if (owner) {
#pragma unroll 1
                for (int k = 0; k < N_HEAD; k++) mbar_expect_tx(bar_q + k * 8, PIECE_BYTES);
                mbar_wait(bar_empty + (TAIL_SLOT + (N_PIECE * PIECE_BYTES - 1) / TILE_BYTES) * 8, 1);
                wait_until(t_start, prm.t_last + PIECE_LAG);
#pragma unroll 1
                for (int k = 0; k < N_PIECE; k++)
                    tma_3d(sb + SM_RING + TAIL_SLOT * TILE_BYTES + k * PIECE_BYTES, k < W2_PIECES ? &tm_w2 : &tm_wc, own * OWN_COLS,
                           (k < W2_PIECES ? k : k - W2_PIECES) * PIECE_ROWS, 0, k < N_HEAD ? bar_q + k * 8 : bar_t + (k - N_HEAD) * 8, pol);
            }
        }
        return;
    }

    if (tid == (N_CONS_WARPS + 1) * 32) {
#pragma unroll 1
        for (int i = 0; i < N_SLOT; i++) mbar_init(bar_empty + i * 8, V_WARPS);
        asm volatile("fence.mbarrier_init.release.cluster;" ::: "memory");
    }
    if (warp >= N_CONS_WARPS + 2 && warp < N_CONS_WARPS + 2 + N_AUX && lane == 0) {
        const uint32_t b0 = bar_t + (warp - (N_CONS_WARPS + 2)) * 17 * 8;
#pragma unroll 1
        for (int i = 0; i < 17; i++) mbar_init(b0 + i * 8, 1);
        asm volatile("fence.mbarrier_init.release.cluster;" ::: "memory");
        if (warp == N_CONS_WARPS + 2) {
#pragma unroll 1
            for (int k = 0; k < WO_ROUNDS; k++) mbar_expect_tx(bar_t + k * 8, odd ? WO_BYTES : PIECE_BYTES);
        }
    }
    __syncwarp();
    uint2 xin = make_uint2(0u, 0u);
    if (warp < 5) xin = *reinterpret_cast<const uint2*>(prm.x + tid * 4);
    volatile uint32_t* s_epoch = reinterpret_cast<volatile uint32_t*>(sp + SM_ML + 60);
    if (tid == 5 * 32) *s_epoch = ll_ld(&g_epoch);

    if (warp == N_CONS_WARPS + 1) {
        const int lc = lane & (OWN_COLS - 1);
        const int col = own * OWN_COLS + lc;
        uint32_t x_lo = 0;
        if (owner) x_lo = reinterpret_cast<const uint16_t*>(prm.x)[col];
        uint16_t* outp = reinterpret_cast<uint16_t*>(prm.out) + col;
        asm volatile("" : "+l"(outp));
        named_sync(6, N_THREADS);
        const uint32_t tag = (*s_epoch + 1u) & 1u;
        if (lane == 0) {
            ll_store(g_xt + cta, (*t_first & ~1u) | tag);
            mbar_arrive(bar_full + 7 * 8);
        }
        {
            const int c = lane < 24 ? lane >> 1 : 0;
            const uint32_t* xf = g_x1 + (cta / FF_GROUP) * FF_GROUP * X1_STRIDE + 192 + (lane & 1) * 192 +
                                 (cta % FF_GROUP) * FF_PER_CTA + c;
            mbar_wait(bar_full + FFN_TILE * 8, 0);
            const float mine = bf16r(ll_poll_sum<16>(xf, X1_STRIDE, tag));
            const float other = __shfl_xor_sync(0xffffffffu, mine, 1);
            const float hv = bf16r(bf16r(silu_f(mine)) * other);
            if (lane < 24 && !(lane & 1)) ll_store(g_xh + cta * FF_PER_CTA + c, __float_as_uint(hv) | tag);
        }
#pragma unroll 1
        for (int b = 0; b < 4; b++) {
            mbar_wait(go_b + b * 8, 0);
            const int h = b * 8 + (lane & 7);
            uint2 v;
            unsigned n = 0;
#pragma unroll 1
            while (true) {
                uint32_t bad = 0;
                v = ll_ld2(g_xs + h * X2_STRIDE);
                ll_check(bad, v.x, tag); ll_check(bad, v.y, tag);
                if (__all_sync(0xffffffffu, (bad & 1u) == 0) || ++n > SPIN_LIMIT) break;
            }
            if (lane < 8) *reinterpret_cast<float2*>(sp + SM_S + h * 8) = make_float2(bf_hi(v.x), ll_val(v.y));
            __syncwarp();
            if (lane == 0) mbar_arrive(bar_s + b * 8);
            if (b == 2) {
                uint32_t due = t_first[0] - t_first[-1] + prm.t_late;
                int late = 0;
#pragma unroll 1
                for (int t = LATE_TILE; t < LATE_TILE + 4; t++) {
                    while (!mbar_try(bar_full + (t & (N_SLOT - 1)) * 8, (t >> 4) & 1) && (int)(now_ns() - due) < MAX_LATE) {}
                    late += min((int)(now_ns() - due), MAX_LATE);
                    due += 2 * prm.step;
                }
                if (lane == 0) ll_store(g_xl + cta, ((uint32_t)late & ~1u) | tag);
                if (!odd && idx < N_LATE) {
                    mbar_wait(bar_full + (LATE_READ & (N_SLOT - 1)) * 8, (LATE_READ >> 4) & 1);
                    uint4 w[1];
                    ll_poll4<1>(w, g_xl + lane * 4, 0, tag);
                    late = __reduce_add_sync(0xffffffffu, (int)(w[0].x + w[0].y + w[0].z + w[0].w)) / (4 * N_CTA);
                    late = min(max(late * LATE_GAIN / 8, 0), MAX_LATE);
                    if (lane < 8) ll_store(g_xm + idx * 32 + lane, ((uint32_t)late & ~1u) | tag);
                }
            }
        }
        {
            const uint32_t w = ll_ld(g_xm + (idx % N_LATE) * 32);
            if (lane == 0 && ((w ^ tag) & 1u) == 0) t_first[-1] = t_first[-1] - w;
        }
        if (owner) {
            uint32_t fin = sb + SM_FIN + lc * (FIN_STRIDE * 4);
            asm volatile("" : "+r"(fin));
            named_sync(5, N_CONS + 32);
            float fp[8];
#pragma unroll
            for (int i = 0; i < 8; i++) fp[i] = __uint_as_float(lds32(sb + SM_FIN + FIN_STRIDE * 64 + lc * 4 + i * 64));
            const float f = ((fp[0] + fp[1]) + (fp[2] + fp[3])) + ((fp[4] + fp[5]) + (fp[6] + fp[7]));
            const uint32_t g_lo = pack_bf16(silu_f(bf16r(f)), 0.f);
            sts32(fin + 72, __uint_as_float(g_lo));
            named_sync(14, N_AUX * 32 + 32);
            const float4 c = lds128(fin + 32), d = lds128(fin + 48);
            const float gathered = ((c.x + c.y) + (c.z + c.w)) + ((d.x + d.y) + (d.z + d.w));
            sts32(fin + 64, gathered);
            named_sync(12, N_CONS + 32);
            const float4 a = lds128(fin), b = lds128(fin + 16);
            const float sum = (((a.x + gathered) + a.y) + (a.z + a.w)) + ((b.x + b.y) + (b.z + b.w));
            uint32_t res;
            asm("{ .reg .b32 t; mul.rn.bf16x2 t, %1, %2; add.rn.bf16x2 %0, %3, t; }"
                : "=r"(res) : "r"(pack_bf16(sum, 0.f)), "r"(g_lo), "r"(x_lo));
            asm volatile("st.global.u16 [%0], %1;" ::"l"(outp), "h"((uint16_t)res) : "memory");
        }
        return;
    }
    if (warp >= N_CONS_WARPS + 2) {
        const int fw = warp - (N_CONS_WARPS + 2);
        named_sync(6, N_THREADS);
        const uint32_t epoch = *s_epoch, tag = (epoch + 1u) & 1u;
        mbar_wait(go_q, 0);
        if (fw == N_AUX - 1) {
            const uint4 v = ll_ld4(g_xt + lane * 4);
            uint32_t bad = 0;
            ll_check(bad, v.x, tag); ll_check(bad, v.y, tag); ll_check(bad, v.z, tag); ll_check(bad, v.w, tag);
            const uint32_t t0 = *t_first;
            int d = max(max((int)(t0 - v.x), (int)(t0 - v.y)), max((int)(t0 - v.z), (int)(t0 - v.w)));
#pragma unroll
            for (int o = 16; o > 0; o >>= 1) d = max(d, __shfl_xor_sync(0xffffffffu, d, o));
            if (__all_sync(0xffffffffu, (bad & 1u) == 0) && lane == 0) t_first[-1] = min(max(d, 0), MAX_SHIFT);
        }
        mbar_wait(bar_full + Q_TILE * 8, 0);
#pragma unroll 1
        for (int h = fw; h < N_HEAD; h += N_AUX) {
            uint4 v[2];
            ll_poll4<2>(v, g_xq + h * D_HEAD + (lane % 24) * 4, 96, tag);
            if (lane < 24) {
                *reinterpret_cast<uint2*>(sp + SM_Q + h * 384 + lane * 8) = upper_halves(v[0]);
                *reinterpret_cast<uint2*>(sp + SM_Q + h * 384 + 192 + lane * 8) = upper_halves(v[1]);
            }
            __syncwarp();
            if (lane == 0) mbar_arrive(bar_q + h * 8);
        }
        if (r == 0 && fw == N_AUX - 1) {
            mbar_wait(go_s, 0);
            const uint32_t* xm = g_x2 + (head * N_CTA + lane) * X2_STRIDE;
            uint2 ml[4];
            unsigned n = 0;
#pragma unroll 1
            while (true) {
                uint32_t bad = 0;
#pragma unroll
                for (int i = 0; i < 4; i++) ml[i] = ll_ld2(xm + i * 32 * X2_STRIDE);
#pragma unroll
                for (int i = 0; i < 4; i++) { ll_check(bad, ml[i].x, tag); ll_check(bad, ml[i].y, tag); }
                if (__all_sync(0xffffffffu, (bad & 1u) == 0) || ++n > SPIN_LIMIT) break;
            }
            float m = fmaxf(fmaxf(bf_hi(ml[0].x), bf_hi(ml[1].x)), fmaxf(bf_hi(ml[2].x), bf_hi(ml[3].x)));
#pragma unroll
            for (int o = 16; o > 0; o >>= 1) m = fmaxf(m, __shfl_xor_sync(0xffffffffu, m, o));
            float den = 0.f;
#pragma unroll
            for (int i = 0; i < 4; i++) den = fmaf(ex2((bf_hi(ml[i].x) - m) * LOG2E), ll_val(ml[i].y), den);
#pragma unroll
            for (int o = 16; o > 0; o >>= 1) den += __shfl_xor_sync(0xffffffffu, den, o);
            if (lane < X2_STRIDE) ll_store(g_xs + head * X2_STRIDE + lane, ll_pack(lane == 0 ? m : rcp(den), tag));
            if (cta == 0 && lane == 0) ll_store(&g_epoch, epoch + 1u);
        }
        if (owner) {
            mbar_wait(go_k, 0);
            uint4 v[3];
            ll_poll4<3>(v, g_xh + fw * 384 + lane * 4, 128, tag);
#pragma unroll
            for (int i = 0; i < 3; i++) *reinterpret_cast<uint2*>(sp + SM_H + (fw * 384 + i * 128 + lane * 4) * 2) = upper_halves(v[i]);
        }
#pragma unroll 1
        for (int s = fw; s < (odd ? WO_ROUNDS : XO_GROUPS); s += N_AUX) {
            const int grp = (odd ? GROUP0 : 0) + s * N_WO + idx;
            mbar_wait(go_o + s * 8, 0);
            if (grp >= (N_HEAD - 1) * 24) {
                const uint32_t c0 = clock();
                while ((uint32_t)clock() - c0 < (uint32_t)O_LAG) {}
            }
            uint4 v[8];
            ll_poll4<8>(v, g_x3 + grp * (N_CTA * 8) + lane * 4, 128, tag);
            float t0 = 0.f, t1 = 0.f, t2 = 0.f, t3 = 0.f;
#pragma unroll
            for (int i = 0; i < 8; i += 2) {
                t0 += ll_val(v[i].x) + ll_val(v[i + 1].x); t1 += ll_val(v[i].y) + ll_val(v[i + 1].y);
                t2 += ll_val(v[i].z) + ll_val(v[i + 1].z); t3 += ll_val(v[i].w) + ll_val(v[i + 1].w);
            }
            const bool u2 = lane & 2, u4 = lane & 4;
            const float a = (u2 ? t2 : t0) + __shfl_xor_sync(0xffffffffu, u2 ? t0 : t2, 2);
            const float b = (u2 ? t3 : t1) + __shfl_xor_sync(0xffffffffu, u2 ? t1 : t3, 2);
            float c = (u4 ? b : a) + __shfl_xor_sync(0xffffffffu, u4 ? a : b, 4);
            c += __shfl_xor_sync(0xffffffffu, c, 8);
            c += __shfl_xor_sync(0xffffffffu, c, 16);
            const int e = 4 * (lane & 1) + (lane & 2) + (lane >> 2);
            if (lane < 8) {
                if (odd) reinterpret_cast<uint16_t*>(sp + SM_O)[s * 8 + e] = (uint16_t)pack_bf16(c, 0.f);
                else ll_store(g_xo + grp * 8 + e, __float_as_uint(bf16r(c)) | tag);
            }
            if (s == fw + N_AUX) named_arrive(3, N_CONS + N_AUX * 32);
        }
        if (odd) named_arrive(13, N_CONS + N_AUX * 32);
        if (owner) {
            mbar_wait(go_o + XO_GROUPS * 8, 0);
            uint4 o[2];
            ll_poll4<2>(o, g_xo + fw * 128 + lane * 4, 512, tag);
#pragma unroll
            for (int i = 0; i < 2; i++)
                *reinterpret_cast<uint2*>(sp + SM_H + (D_FF + i * 512 + fw * 128 + lane * 4) * 2) = upper_halves(o[i]);
            named_arrive(4, N_AUX * 32 + N_CONS);
            const uint32_t* p = g_x5 + (own * N_WO + fw * (N_WO / N_AUX)) * OWN_COLS + lane;
            uint32_t dst = sb + SM_FIN + ((lane & 15) * FIN_STRIDE + 8 + fw * 2 + (lane >> 4)) * 4;
            uint32_t t_x5 = prm.t_last + X5_LAG;
            asm volatile("" : "+r"(dst), "+l"(p), "+r"(t_x5));
            mbar_wait(bar_q + X5_PIECE * 8, 1);
            wait_until(t_first[0] - t_first[-1], t_x5);
            unsigned n = 0;
#pragma unroll 1
            while (true) {
                uint32_t w[8];
#pragma unroll
                for (int i = 0; i < 8; i++) w[i] = ll_ld(p + i * 32);
                uint32_t bad[4];
#pragma unroll
                for (int i = 0; i < 4; i++)
                    asm("lop3.b32 %0, %1, %2, %3, 0x7E;" : "=r"(bad[i]) : "r"(w[2 * i]), "r"(w[2 * i + 1]), "r"(tag));
                const float c = ((ll_val(w[0]) + ll_val(w[1])) + (ll_val(w[2]) + ll_val(w[3]))) +
                                ((ll_val(w[4]) + ll_val(w[5])) + (ll_val(w[6]) + ll_val(w[7])));
                sts32(dst, c);
                if (__all_sync(0xffffffffu, !(((bad[0] | bad[1]) | (bad[2] | bad[3])) & 1u)) || ++n > SPIN_LIMIT) break;
            }
            named_arrive(14, N_AUX * 32 + 32);
        }
        return;
    }

    float* sml = reinterpret_cast<float*>(sp + SM_ML);
    if (warp < 5) {
        const uint2 u = xin;
        float s1 = (bf_lo(u.x) + bf_hi(u.x)) + (bf_lo(u.y) + bf_hi(u.y));
#pragma unroll
        for (int o = 16; o > 0; o >>= 1) s1 += __shfl_xor_sync(0xffffffffu, s1, o);
        if (lane == 0) sml[warp] = s1;
        named_sync(10, 160);
        const float mean = (((sml[0] + sml[1]) + (sml[2] + sml[3])) + sml[4]) * (1.f / D_MODEL);
        const float a = bf_lo(u.x) - mean, b = bf_hi(u.x) - mean, c = bf_lo(u.y) - mean, d = bf_hi(u.y) - mean;
        float s2 = fmaf(a, a, fmaf(b, b, fmaf(c, c, d * d)));
#pragma unroll
        for (int o = 16; o > 0; o >>= 1) s2 += __shfl_xor_sync(0xffffffffu, s2, o);
        if (lane == 0) sml[8 + warp] = s2;
        named_sync(10, 160);
        const float var = (((sml[8] + sml[9]) + (sml[10] + sml[11])) + sml[12]) * (1.f / D_MODEL);
        const float mean_b = bf16r(mean);
        float den;
        asm("sqrt.approx.f32 %0, %1;" : "=f"(den) : "f"(bf16r(bf16r(var) + 1e-5f)));
        const float inv = rcp(bf16r(den));
        const uint32_t d0 = pack_bf16(bf_lo(u.x) - mean_b, bf_hi(u.x) - mean_b);
        const uint32_t d1 = pack_bf16(bf_lo(u.y) - mean_b, bf_hi(u.y) - mean_b);
        *reinterpret_cast<uint2*>(sp + SM_XN + tid * 8) =
            make_uint2(pack_bf16(bf_lo(d0) * inv, bf_hi(d0) * inv), pack_bf16(bf_lo(d1) * inv, bf_hi(d1) * inv));
    }
    named_sync(6, N_THREADS);
    const uint32_t tag = (*s_epoch + 1u) & 1u;
    if (tid < Q_PER_CTA) ll_store(g_xq + cta * Q_PER_CTA + tid, tag ^ 1u);

    const int q4 = lane & 3, g8 = lane >> 2;
    const int rowT = (lane & 7) + ((lane >> 4) << 3), hiT = (lane >> 3) & 1;

    uint32_t* x1 = g_x1 + cta * X1_STRIDE + q4 * 8 + g8;
    if (warp < 6) {
        const uint32_t xn_addr = sb + SM_XN + (r * ROWS_PER_CTA + 2 * q4) * 2;
        const int line = 3 * rowT + (warp >> 1);
        const uint32_t o0 = (line * 128 + ((hiT ^ (line & 7)) << 4)) ^ ((warp & 1) << 6), o1 = o0 ^ 32;
        float acc[2][4] = {};
#pragma unroll 1
        for (int t = 0; t < 5; t++) {
            mbar_wait(bar_full + t * 8, 0);
            const uint32_t tb = sb + SM_RING + t * TILE_BYTES;
#pragma unroll
            for (int kk = 0; kk < 2; kk++) {
                const uint32_t b0 = lds32(xn_addr + (t * 32 + kk * 16) * 2);
                const uint32_t b1 = lds32(xn_addr + (t * 32 + kk * 16 + 8) * 2);
                uint32_t a[4];
                ldsm_x4_t(a, tb + kk * 6144 + o0);
                mma_bf16(acc[0], a, b0, b1);
                ldsm_x4_t(a, tb + kk * 6144 + o1);
                mma_bf16(acc[1], a, b0, b1);
            }
        }
        ll_store(x1 + warp * 32, ll_pack(pick4(acc[0][0], acc[0][2], acc[1][0], acc[1][2], q4), tag));
        mbar_wait(bar_full + T_W3 * 8, 0);
        named_sync(11, 192);
        if (tid < 5 * V_WARPS) mbar_arrive(bar_empty + (tid / V_WARPS) * 8);
        if (tid < Q_PER_CTA) {
            const float qv = ll_poll_sum<4>(g_x1 + head * SPLIT * X1_STRIDE + r * Q_PER_CTA + tid, X1_STRIDE, tag);
            ll_store(g_xq + cta * Q_PER_CTA + tid, __float_as_uint(bf16r(qv)) | tag);
        }
        __syncwarp();
        if (tid == 0) mbar_arrive(go_q);
    } else {
        float acc[12][4] = {};
        mbar_wait(bar_full + (T_W1 + warp - 6) * 8, 0);
        const uint32_t xf_addr = sb + SM_XN + ((cta % FF_GROUP) * FF_ROWS + 2 * q4) * 2;
        uint32_t ad[3];
#pragma unroll
        for (int j = 0; j < 3; j++)
            ad[j] = sb + SM_RING + T_W1 * TILE_BYTES + (warp - 6) * W13_BYTES + (3 * rowT + j) * 128 + ((hiT ^ ((3 * rowT + j) & 7)) << 4);
#pragma unroll 1
        for (int ks = 0; ks < 3; ks++) {
            const uint32_t b0 = lds32(xf_addr + ks * 32);
            uint32_t b1 = 0u, step = ks * 6144;
            if (ks < 2) b1 = lds32(xf_addr + ks * 32 + 16);
            else if (lane >= 16) step -= 8 * 384;
#pragma unroll
            for (int mt = 0; mt < 12; mt++) {
                uint32_t a[4];
                ldsm_x4_t(a, (ad[mt >> 2] + step) ^ ((mt & 3) << 5));
                mma_bf16(acc[mt], a, b0, b1);
            }
        }
#pragma unroll
        for (int i = 0; i < 6; i++)
            ll_store(x1 + 192 + (warp - 6) * 192 + i * 32,
                     ll_pack(pick4(acc[2 * i][0], acc[2 * i][2], acc[2 * i + 1][0], acc[2 * i + 1][2], q4), tag));
        named_sync(7, 64);
        if (tid >= 192 && tid < 192 + 3 * V_WARPS) mbar_arrive(bar_empty + (T_W1 + (tid - 192) / V_WARPS) * 8);
    }
    named_sync(1, N_CONS);

    {
        const int rowN = (lane & 7) + (((lane >> 3) & 1) << 3), hiN = lane >> 4;
#pragma unroll 1
        for (int h = warp; h < N_HEAD; h += N_CONS_WARPS) {
            const int t = T_K + h, slot = t & (N_SLOT - 1);
            mbar_wait(bar_q + h * 8, 0);
            mbar_wait(bar_full + slot * 8, (t >> 4) & 1);
            const uint32_t tb = sb + SM_RING + slot * TILE_BYTES;
            const int swz = h < N_PLAIN ? 0 : 7;
            float acc[2][2][4] = {};
#pragma unroll 1
            for (int j = 0; j < 3; j++) {
                const uint32_t oj = tb + (3 * rowN + j) * 128 + ((hiN ^ ((3 * rowN + j) & swz)) << 4);
                const uint32_t qa = sb + SM_Q + h * 384 + (j * 64 + 2 * q4) * 2;
#pragma unroll
                for (int k = 0; k < 4; k++) {
                    const uint32_t b0 = lds32(qa + k * 32), b1 = lds32(qa + k * 32 + 16);
                    uint32_t a[4];
                    ldsm_x4(a, oj ^ (k << 5));
                    mma_bf16(acc[0][k & 1], a, b0, b1);
                    ldsm_x4(a, (oj + 6144) ^ (k << 5));
                    mma_bf16(acc[1][k & 1], a, b0, b1);
                }
            }
            __syncwarp();
            if (lane < V_WARPS) mbar_arrive(bar_empty + slot * 8);
            const float raw = pick4(acc[0][0][0] + acc[0][1][0], acc[0][0][2] + acc[0][1][2],
                                    acc[1][0][0] + acc[1][1][0], acc[1][0][2] + acc[1][1][2], q4);
            const float sc = bf16r(bf16r(raw) * 0.07216878364870323f);
            float mw = sc;
#pragma unroll
            for (int o = 16; o > 0; o >>= 1) mw = fmaxf(mw, __shfl_xor_sync(0xffffffffu, mw, o));
            const float p = ex2((sc - mw) * LOG2E);
            reinterpret_cast<uint16_t*>(sp + SM_P)[h * 32 + q4 * 8 + g8] = (uint16_t)pack_bf16(p, 0.f);
            float lw = p;
#pragma unroll
            for (int o = 16; o > 0; o >>= 1) lw += __shfl_xor_sync(0xffffffffu, lw, o);
            if (lane < X2_STRIDE) ll_store(g_x2 + (h * N_CTA + cta) * X2_STRIDE + lane, ll_pack(lane == 0 ? mw : lw, tag));
            if (lane == 0) {
                reinterpret_cast<float*>(sp + SM_M)[h] = mw;
                if (h == head + S_DELAY) mbar_arrive(go_s);
                if (h >= 23 && (h & 7) == 7) mbar_arrive(go_b + ((h >> 3) - 2) * 8);
            }
        }
    }
    if (odd && q4 < 2) {
#pragma unroll
        for (int j = 0; j < 5; j++) ll_store(g_x5 + ((j * 8 + warp) * N_WO + idx) * OWN_COLS + q4 * 8 + g8, tag ^ 1u);
    }
    named_sync(1, N_CONS);
    if (tid == 0) mbar_arrive(go_k);

    if (warp < V_WARPS) {
        const int line = 3 * rowT + (warp >> 1);
        const uint32_t o0 = (line * 128 + ((hiT ^ (line & 7)) << 4)) ^ ((warp & 1) << 6), o1 = o0 ^ 32;
        uint32_t* x3 = g_x3 + ((warp * 4 + q4) * N_CTA + cta) * 8 + g8;
#pragma unroll
        for (int h = N_HEAD - O_RACING; h < N_HEAD; h++) ll_store(x3 + h * X3_HEAD, tag ^ 1u);
        int s_next = 0, h_next = ((odd ? GROUP0 : 0) + idx) / 24 + O_DELAY;
#pragma unroll 1
        for (int h = 0; h < N_HEAD; h++) {
            const int slot = (T_V + h) & (N_SLOT - 1);
            if ((h & 7) == 0) mbar_wait(bar_s + h, 0);
            const float2 ms = *reinterpret_cast<const float2*>(sp + SM_S + h * 8);
            const float scale = ex2((reinterpret_cast<const float*>(sp + SM_M)[h] - ms.x) * LOG2E) * ms.y;
            mbar_wait(bar_full + slot * 8, ((T_V + h) >> 4) & 1);
            const uint32_t tb = sb + SM_RING + slot * TILE_BYTES;
            const uint32_t pa = sb + SM_P + (h * 32 + 2 * q4) * 2;
            float oacc[2][2][4] = {};
#pragma unroll
            for (int kk = 0; kk < 2; kk++) {
                const uint32_t b0 = lds32(pa + kk * 32), b1 = lds32(pa + kk * 32 + 16);
                uint32_t a[4];
                ldsm_x4_t(a, tb + kk * 6144 + o0);
                mma_bf16(oacc[0][kk], a, b0, b1);
                ldsm_x4_t(a, tb + kk * 6144 + o1);
                mma_bf16(oacc[1][kk], a, b0, b1);
            }
            __syncwarp();
            if (lane == 0) mbar_arrive(bar_empty + slot * 8);
            const float v = pick4(oacc[0][0][0] + oacc[0][1][0], oacc[0][0][2] + oacc[0][1][2],
                                  oacc[1][0][0] + oacc[1][1][0], oacc[1][0][2] + oacc[1][1][2], q4);
            ll_store(x3 + h * X3_HEAD, ll_pack(v * scale, tag));
            if (tid == 0) {
                if (h == head + S_DELAY - N_HEAD) mbar_arrive(go_s);
                if (h == 10 || h == 21) mbar_arrive(go_b + (h == 10 ? 2 : 3) * 8);
                while (h == h_next) {
                    mbar_arrive(go_o + s_next * 8);
                    s_next++;
                    if (odd) h_next = s_next < WO_ROUNDS ? min((GROUP0 + s_next * N_WO + idx) / 24 + O_DELAY, N_HEAD - 1) : -1;
                    else h_next = s_next < XO_GROUPS ? (s_next * N_WO + idx) / 24 + O_DELAY : s_next == XO_GROUPS ? XO_TILE : -1;
                }
            }
        }
    }

    constexpr int STEPS = N_PIECE / N_CONS_WARPS, W2_STEPS = W2_PIECES / N_CONS_WARPS;
    uint32_t hb[STEPS][4][2];
    if (owner) {
        named_sync(4, N_AUX * 32 + N_CONS);
#pragma unroll
        for (int k = 0; k < STEPS; k++)
#pragma unroll
            for (int i = 0; i < 4; i++) {
                const uint32_t ha = sb + SM_H + ((k * N_CONS_WARPS + warp) * PIECE_ROWS + i * 16 + 2 * q4) * 2;
                hb[k][i][0] = lds32(ha);
                hb[k][i][1] = lds32(ha + 16);
            }
    }

    if (odd) {
        uint32_t* x5 = g_x5 + (warp * N_WO + idx) * OWN_COLS + (q4 & 1) * 8 + g8;
        asm volatile("" : "+l"(x5));
        named_sync(3, N_CONS + N_AUX * 32);
        float acc[5][4] = {};
        uint32_t wa = sb + SM_RING + TAIL_SLOT * TILE_BYTES + (lane >> 4) * 2048 + (warp >> 2) * 1024 + (lane & 7) * 128 +
                      (((((warp & 3) << 1) | hiT) ^ (lane & 7)) << 4);
        auto multiply = [&](int p) {
            const uint32_t b0 = lds32(sb + SM_O + (p * 8 + 2 * q4) * 2);
            mbar_wait(bar_t + p * 8, 0);
            uint32_t a0[4], a1[4], a2[2];
            ldsm_x4_t(a0, wa);
            ldsm_x4_t(a1, wa + 4096);
            ldsm_x2_t(a2, wa + 8192);
            mma_bf16_k8(acc[0], a0[0], a0[1], b0);
            mma_bf16_k8(acc[1], a0[2], a0[3], b0);
            mma_bf16_k8(acc[2], a1[0], a1[1], b0);
            mma_bf16_k8(acc[3], a1[2], a1[3], b0);
            mma_bf16_k8(acc[4], a2[0], a2[1], b0);
        };
#pragma unroll 1
        for (int p = 0; p < WO_ROUNDS - 1; p++) {
            if (p == 2 * N_AUX) named_sync(13, N_CONS + N_AUX * 32);
            multiply(p);
            wa += p == WO_WRAP - 1 ? -(TAIL_SLOT * TILE_BYTES + (WO_WRAP - 1) * WO_BYTES) : WO_BYTES;
        }
        multiply(WO_ROUNDS - 1);
#pragma unroll
        for (int j = 0; j < 5; j++) ll_store(x5 + j * 8 * N_WO * OWN_COLS, ll_pack(q4 & 1 ? acc[j][2] : acc[j][0], tag));
    }

    if (owner) {
        float acc[4][4] = {};
        const uint32_t wa = sb + SM_RING + TAIL_SLOT * TILE_BYTES + (warp * PIECE_ROWS + rowT) * 32 + ((hiT ^ ((lane >> 2) & 1)) << 4);
        uint32_t fin_f = sb + SM_FIN + (16 * FIN_STRIDE + warp * 16 + (q4 & 1) * 8 + g8) * 4;
        uint32_t fin_s = sb + SM_FIN + (((q4 & 1) * 8 + g8) * FIN_STRIDE + warp) * 4;
        uint32_t bar = bar_q + warp * 8;
        asm volatile("" : "+r"(fin_f), "+r"(fin_s), "+r"(bar));
#pragma unroll
        for (int k = 0; k < STEPS; k++) {
            if (k < N_HEAD / N_CONS_WARPS) mbar_wait(bar + k * N_CONS_WARPS * 8, 1);
            else mbar_wait(bar - (bar_q - bar_t), 0);
            uint32_t a[4][4];
#pragma unroll
            for (int i = 0; i < 4; i++) ldsm_x4_t(a[i], wa + k * N_CONS_WARPS * PIECE_BYTES + i * 512);
#pragma unroll
            for (int i = 0; i < 4; i++) mma_bf16(acc[i], a[i], hb[k][i][0], hb[k][i][1]);
            if (k == W2_STEPS - 1 || k == STEPS - 1) {
                const float part = q4 ? (acc[0][2] + acc[1][2]) + (acc[2][2] + acc[3][2]) : (acc[0][0] + acc[1][0]) + (acc[2][0] + acc[3][0]);
                if (q4 < 2) sts32(k < W2_STEPS ? fin_f : fin_s, part);
                named_arrive(k < W2_STEPS ? 5 : 12, N_CONS + 32);
#pragma unroll
                for (int i = 0; i < 4; i++) acc[0][i] = acc[1][i] = acc[2][i] = acc[3][i] = 0.f;
            }
        }
    }
    return;
}


typedef CUresult (*EncodeTiledFn)(CUtensorMap*, CUtensorMapDataType, cuuint32_t, void*, const cuuint64_t*,
                                  const cuuint64_t*, const cuuint32_t*, const cuuint32_t*, CUtensorMapInterleave,
                                  CUtensorMapSwizzle, CUtensorMapL2promotion, CUtensorMapFloatOOBfill);

void encode_map(EncodeTiledFn fn, CUtensorMap* m, const void* base, cuuint64_t d1, cuuint64_t d2, cuuint64_t s1,
                cuuint64_t s2, cuuint32_t b1, cuuint32_t b2) {
    const cuuint64_t dims[3] = {64, d1, d2};
    const cuuint64_t strides[2] = {s1, s2};
    const cuuint32_t box[3] = {64, b1, b2};
    const cuuint32_t estr[3] = {1, 1, 1};
    fn(m, CU_TENSOR_MAP_DATA_TYPE_BFLOAT16, 3, const_cast<void*>(base), dims, strides, box, estr,
       CU_TENSOR_MAP_INTERLEAVE_NONE, CU_TENSOR_MAP_SWIZZLE_128B, CU_TENSOR_MAP_L2_PROMOTION_NONE,
       CU_TENSOR_MAP_FLOAT_OOB_FILL_NONE);
}

}

extern "C" void kernel_launch(void* const* d_in, const int* in_sizes, int n_in, void* d_out, int out_size) {
    (void)in_sizes; (void)n_in; (void)out_size;
    static EncodeTiledFn encode = nullptr;
    static double pace_scale = 1.0;
    if (!encode) {
        int dev = 0, mem_khz = 0, bus_bits = 0;
        cudaGetDevice(&dev);
        cudaDeviceGetAttribute(&mem_khz, cudaDevAttrMemoryClockRate, dev);
        cudaDeviceGetAttribute(&bus_bits, cudaDevAttrGlobalMemoryBusWidth, dev);
        const double peak_gbs = 2.0 * mem_khz * 1e-6 * bus_bits / 8.0;
        if (peak_gbs > 0.0) pace_scale = PACE_REF_GBS / peak_gbs;
        void* fn = nullptr;
        cudaDriverEntryPointQueryResult qr;
        cudaGetDriverEntryPoint("cuTensorMapEncodeTiled", &fn, cudaEnableDefault, &qr);
        encode = reinterpret_cast<EncodeTiledFn>(fn);
        cudaFuncSetAttribute(fused_decode_kernel, cudaFuncAttributeMaxDynamicSharedMemorySize, SM_ALLOC);
    }
    CUtensorMap tm_k, tm_v, tm_wq, tm_w1, tm_w3, tm_wo, tm_w2, tm_wc;
    {
        const cuuint64_t dims[3] = {D_MODEL, D_FF, 1};
        const cuuint64_t strides[2] = {D_MODEL * 2, (cuuint64_t)D_MODEL * 2 * D_FF};
        const cuuint32_t box[3] = {OWN_COLS, PIECE_ROWS, 1};
        const cuuint32_t estr[3] = {1, 1, 1};
        encode(&tm_w2, CU_TENSOR_MAP_DATA_TYPE_BFLOAT16, 3, d_in[8], dims, strides, box, estr, CU_TENSOR_MAP_INTERLEAVE_NONE,
               CU_TENSOR_MAP_SWIZZLE_32B, CU_TENSOR_MAP_L2_PROMOTION_NONE, CU_TENSOR_MAP_FLOAT_OOB_FILL_NONE);
        encode(&tm_wc, CU_TENSOR_MAP_DATA_TYPE_BFLOAT16, 3, d_in[4], dims, strides, box, estr, CU_TENSOR_MAP_INTERLEAVE_NONE,
               CU_TENSOR_MAP_SWIZZLE_32B, CU_TENSOR_MAP_L2_PROMOTION_NONE, CU_TENSOR_MAP_FLOAT_OOB_FILL_NONE);
    }
    encode_map(encode, &tm_k, d_in[1], 3, (cuuint64_t)N_HEAD * SEQ, 128, D_HEAD * 2, 3, SUB_ROWS);
    encode_map(encode, &tm_v, d_in[2], 3, (cuuint64_t)N_HEAD * SEQ, 128, D_HEAD * 2, 3, SUB_ROWS);
    encode_map(encode, &tm_wq, d_in[3], N_HEAD * 3, D_MODEL, 128, N_HEAD * D_HEAD * 2, 3, SUB_ROWS);
    encode_map(encode, &tm_w1, d_in[6], D_FF / 64, D_MODEL, 128, D_FF * 2, 3, 8);
    encode_map(encode, &tm_w3, d_in[7], D_FF / 64, D_MODEL, 128, D_FF * 2, 3, 8);
    encode_map(encode, &tm_wo, d_in[4], N_HEAD * D_HEAD, D_MODEL / 64, D_MODEL * 2, 128, 8, 10);
    Params prm;
    prm.x = static_cast<const __nv_bfloat16*>(d_in[0]);
    prm.k_win = static_cast<const __nv_bfloat16*>(d_in[1]) + (size_t)(SEQ - WIN) * D_HEAD;
    prm.out = static_cast<__nv_bfloat16*>(d_out);
    auto step = [&](double pace, double bytes) { return (uint32_t)(pace * pace_scale * bytes / TILE_BYTES + 0.01); };
    prm.step = step(PACE, SUB_ROWS * 384);
    prm.step_ffn = step(PACE, 8 * 384);
    prm.step_wo = step(PACE_WO, WO_BYTES / 2);
    prm.step_start = (uint32_t)(PACE_START * pace_scale + 0.5);
    prm.step_ahead = step(PACE_AHEAD, AHEAD_ROWS * D_MODEL);
    const uint32_t t_k = prm.step_start + 2 * T_W1 * prm.step + 2 * (FF_ROWS / 8) * prm.step_ffn;
    prm.t_late = t_k + (2 * (LATE_TILE - T_K - N_PLAIN) + 1) * prm.step + LATE_NS;
    prm.t_last = t_k + 2 * (T_END - T_K - N_PLAIN) * prm.step + (WO_ROUNDS - 1) * prm.step_wo;
    prm.w2 = static_cast<const char*>(d_in[8]);
    prm.wo = static_cast<const char*>(d_in[4]);
    fused_decode_kernel<<<N_CTA, N_THREADS, SM_ALLOC, cudaStreamPerThread>>>(
        prm, tm_wq, tm_w1, tm_w3, tm_k, tm_v, tm_wo, tm_w2, tm_wc);
}
```

```cpp
#include <cuda_runtime.h>
#include <cuda_bf16.h>
#include <cuda.h>
#include <stdint.h>

namespace {

constexpr int D_MODEL = 640;
constexpr int N_HEAD = 32;
constexpr int D_HEAD = 192;
constexpr int SEQ = 32768;
constexpr int WIN = 4096;
constexpr int D_FF = 1536;

constexpr int SPLIT = 4;
constexpr int N_CTA = N_HEAD * SPLIT;
constexpr int TILE_ROWS = WIN / N_CTA;
constexpr int TILE_BYTES = TILE_ROWS * D_HEAD * 2;
constexpr int N_SLOT = 16;

constexpr int ROWS_PER_CTA = D_MODEL / SPLIT;
constexpr int FF_GROUP = 16;
constexpr int FF_ROWS = D_MODEL / FF_GROUP;
constexpr int FF_PER_CTA = D_FF / N_CTA;
constexpr int Q_PER_CTA = D_HEAD / SPLIT;

constexpr int OWN_COLS = 16;
constexpr int N_OWN = D_MODEL / OWN_COLS;
constexpr int XO_ROWS = 1024;
constexpr int PIECE_ROWS = 64;
constexpr int PIECE_BYTES = PIECE_ROWS * OWN_COLS * 2;
constexpr int W2_PIECES = D_FF / PIECE_ROWS, N_PIECE = W2_PIECES + XO_ROWS / PIECE_ROWS;
constexpr int N_WO = N_CTA / 2;
constexpr int GROUP0 = XO_ROWS / 8;
constexpr int WO_ROUNDS = (N_HEAD * D_HEAD / 8 - GROUP0) / N_WO;
constexpr int WO_BYTES = 8 * D_MODEL * 2;
constexpr int XO_GROUPS = GROUP0 / N_WO;
constexpr int AHEAD_ROWS = 4;
constexpr int AHEAD_FROM = 4, AHEAD_W2 = D_FF / (N_WO * AHEAD_ROWS), AHEAD_END = AHEAD_W2 + XO_ROWS / (N_WO * AHEAD_ROWS);

constexpr int T_W1 = 5, T_W3 = 6;
constexpr int T_K = 8;
constexpr int T_V = T_K + N_HEAD;
constexpr int T_END = T_V + N_HEAD;
constexpr int N_PLAIN = 2;

constexpr int W13_BYTES = FF_ROWS * 192 * 2;
constexpr int TAIL_SLOT = T_END % N_SLOT;
constexpr int WO_WRAP = 9;

constexpr int N_CONS_WARPS = 8;
constexpr int N_CONS = N_CONS_WARPS * 32;
constexpr int N_AUX = 4;
constexpr int N_THREADS = N_CONS + 64 + N_AUX * 32;

constexpr double PACE = 484, PACE_WO = 480, PACE_REF_GBS = 3352.32;
constexpr double PACE_START = 250;
constexpr int PIECE_LAG = 130, AHEAD_LAG = 640, X5_LAG = 1540;
constexpr double PACE_AHEAD = 490;
constexpr int INFLIGHT = 5;
constexpr int SUB_ROWS = 16;
constexpr int MAX_SHIFT = 400;
constexpr int LATE_TILE = 49, LATE_NS = 1205, LATE_GAIN = 10, MAX_LATE = 2000;
constexpr int N_LATE = 8;

constexpr int X1_STRIDE = 576;
constexpr int X2_STRIDE = 8;
constexpr int X3_HEAD = N_CTA * D_HEAD;
constexpr int FIN_STRIDE = 20;
constexpr int V_WARPS = 6;
constexpr int Q_TILE = 12;
constexpr int FFN_TILE = 15;
constexpr int S_DELAY = 12;
constexpr int O_DELAY = 4;
constexpr int O_RACING = 6;
constexpr int O_LAG = 700;
constexpr int XO_TILE = 18;
constexpr int X5_PIECE = 12;
constexpr int LATE_LAG = 300;
constexpr int DELAY_TILE = 57;

constexpr unsigned SPIN_LIMIT = 1u << 22;

constexpr int SM_RING = 0;
constexpr int SM_H = N_SLOT * TILE_BYTES;
constexpr int SM_BAR = SM_H + (D_FF + XO_ROWS) * 2;
constexpr int SM_XN = SM_BAR + 832;
constexpr int SM_Q = SM_XN + 1280;
constexpr int SM_O = SM_Q + N_HEAD * 384;
constexpr int SM_ML = SM_O + 192;
constexpr int SM_M = SM_ML + 64;
constexpr int SM_S = SM_M + 128;
constexpr int SM_FIN = SM_S + 256;
constexpr int SM_P = SM_FIN + 16 * FIN_STRIDE * 4 + 512;
constexpr int SM_ALLOC = SM_P + 2048 + 1024;
static_assert(SM_ALLOC <= 232448, "shared memory");

__device__ uint32_t g_epoch;
__device__ __align__(128) uint32_t g_x1[N_CTA * X1_STRIDE];
__device__ __align__(128) uint32_t g_xq[N_HEAD * D_HEAD];
__device__ __align__(128) uint32_t g_x2[N_HEAD * N_CTA * X2_STRIDE];
__device__ __align__(128) uint32_t g_xs[N_HEAD * X2_STRIDE];
__device__ __align__(128) uint32_t g_x3[N_HEAD * X3_HEAD];
__device__ __align__(128) uint32_t g_xh[D_FF];
__device__ __align__(128) uint32_t g_xt[N_CTA];
__device__ __align__(128) uint32_t g_xl[N_CTA];
__device__ __align__(128) uint32_t g_xm[N_LATE * 32];
__device__ __align__(128) uint32_t g_xo[XO_ROWS];
__device__ __align__(128) uint32_t g_x5[N_OWN * N_WO * OWN_COLS];

__device__ __forceinline__ uint32_t smem_u32(const void* p) { return (uint32_t)__cvta_generic_to_shared(p); }

__device__ __forceinline__ void mbar_init(uint32_t bar, uint32_t cnt) {
    asm volatile("mbarrier.init.shared::cta.b64 [%0], %1;" ::"r"(bar), "r"(cnt) : "memory");
}
__device__ __forceinline__ void mbar_expect_tx(uint32_t bar, uint32_t bytes) {
    asm volatile("mbarrier.arrive.expect_tx.shared::cta.b64 _, [%0], %1;" ::"r"(bar), "r"(bytes) : "memory");
}
__device__ __forceinline__ void mbar_arrive(uint32_t bar) {
    asm volatile("mbarrier.arrive.shared::cta.b64 _, [%0];" ::"r"(bar) : "memory");
}
__device__ __forceinline__ void mbar_wait(uint32_t bar, uint32_t parity) {
    asm volatile(
        "{\n.reg .pred p;\n.reg .u32 n;\n"
        "mov.u32 n, 0;\n"
        "WAIT_LOOP:\n"
        "mbarrier.try_wait.parity.shared::cta.b64 p, [%0], %1;\n"
        "@p bra WAIT_DONE;\n"
        "add.u32 n, n, 1;\n"
        "setp.lt.u32 p, n, %2;\n"
        "@p bra WAIT_LOOP;\n"
        "WAIT_DONE:\n}"
        ::"r"(bar), "r"(parity), "n"(SPIN_LIMIT) : "memory");
}
__device__ __forceinline__ bool mbar_try(uint32_t bar, uint32_t parity) {
    uint32_t ok;
    asm volatile("{ .reg .pred p; mbarrier.try_wait.parity.shared::cta.b64 p, [%1], %2; selp.u32 %0, 1, 0, p; }"
                 : "=r"(ok) : "r"(bar), "r"(parity) : "memory");
    return ok;
}
__device__ __forceinline__ void named_sync(int id, int n) {
    asm volatile("bar.sync %0, %1;" ::"r"(id), "r"(n) : "memory");
}
__device__ __forceinline__ void named_arrive(int id, int n) {
    asm volatile("bar.arrive %0, %1;" ::"r"(id), "r"(n) : "memory");
}
__device__ __forceinline__ bool elect_one() {
    uint32_t pred = 0;
    asm volatile("{ .reg .pred p; elect.sync _|p, 0xffffffff; @p mov.u32 %0, 1; }" : "+r"(pred));
    return pred;
}
__device__ __forceinline__ uint64_t stream_policy() {
    uint64_t pol;
    asm volatile("createpolicy.fractional.L2::evict_first.b64 %0, 1.0;" : "=l"(pol));
    return pol;
}
__device__ __forceinline__ void bulk_load(uint32_t dst, const void* src, uint32_t bytes, uint32_t bar, uint64_t pol) {
    asm volatile("cp.async.bulk.shared::cluster.global.mbarrier::complete_tx::bytes.L2::cache_hint [%0], [%1], %2, [%3], %4;"
                 ::"r"(dst), "l"(src), "r"(bytes), "r"(bar), "l"(pol) : "memory");
}
__device__ __forceinline__ void tma_3d(uint32_t dst, const CUtensorMap* tm, int c0, int c1, int c2, uint32_t bar, uint64_t pol) {
    asm volatile("cp.async.bulk.tensor.3d.shared::cluster.global.mbarrier::complete_tx::bytes.L2::cache_hint [%0], [%1, {%3, %4, %5}], [%2], %6;"
                 ::"r"(dst), "l"(tm), "r"(bar), "r"(c0), "r"(c1), "r"(c2), "l"(pol) : "memory");
}
__device__ __forceinline__ void prefetch_tmap(const CUtensorMap* tm) {
    asm volatile("prefetch.tensormap [%0];" ::"l"(tm) : "memory");
}
__device__ __forceinline__ void ldsm_x4(uint32_t (&r)[4], uint32_t addr) {
    asm volatile("ldmatrix.sync.aligned.m8n8.x4.shared.b16 {%0,%1,%2,%3}, [%4];"
                 : "=r"(r[0]), "=r"(r[1]), "=r"(r[2]), "=r"(r[3]) : "r"(addr) : "memory");
}
__device__ __forceinline__ void ldsm_x4_t(uint32_t (&r)[4], uint32_t addr) {
    asm volatile("ldmatrix.sync.aligned.m8n8.x4.trans.shared.b16 {%0,%1,%2,%3}, [%4];"
                 : "=r"(r[0]), "=r"(r[1]), "=r"(r[2]), "=r"(r[3]) : "r"(addr) : "memory");
}
__device__ __forceinline__ void mma_bf16(float (&c)[4], const uint32_t (&a)[4], uint32_t b0, uint32_t b1) {
    asm volatile("mma.sync.aligned.m16n8k16.row.col.f32.bf16.bf16.f32 {%0,%1,%2,%3}, {%4,%5,%6,%7}, {%8,%9}, {%0,%1,%2,%3};"
                 : "+f"(c[0]), "+f"(c[1]), "+f"(c[2]), "+f"(c[3])
                 : "r"(a[0]), "r"(a[1]), "r"(a[2]), "r"(a[3]), "r"(b0), "r"(b1));
}
__device__ __forceinline__ void mma_bf16_k8(float (&c)[4], uint32_t a0, uint32_t a1, uint32_t b0) {
    asm volatile("mma.sync.aligned.m16n8k8.row.col.f32.bf16.bf16.f32 {%0,%1,%2,%3}, {%4,%5}, {%6}, {%0,%1,%2,%3};"
                 : "+f"(c[0]), "+f"(c[1]), "+f"(c[2]), "+f"(c[3]) : "r"(a0), "r"(a1), "r"(b0));
}
__device__ __forceinline__ void ldsm_x2_t(uint32_t (&r)[2], uint32_t addr) {
    asm volatile("ldmatrix.sync.aligned.m8n8.x2.trans.shared.b16 {%0,%1}, [%2];" : "=r"(r[0]), "=r"(r[1]) : "r"(addr) : "memory");
}
__device__ __forceinline__ float bf16r(float v) {
    uint32_t r;
    asm("cvt.rn.bf16x2.f32 %0, %1, %2;" : "=r"(r) : "f"(v), "f"(0.f));
    return __uint_as_float(r);
}
__device__ __forceinline__ uint32_t lds32(uint32_t addr) {
    uint32_t v;
    asm volatile("ld.shared.b32 %0, [%1];" : "=r"(v) : "r"(addr) : "memory");
    return v;
}
__device__ __forceinline__ float4 lds128(uint32_t addr) {
    float4 v;
    asm volatile("ld.shared.v4.f32 {%0,%1,%2,%3}, [%4];" : "=f"(v.x), "=f"(v.y), "=f"(v.z), "=f"(v.w) : "r"(addr) : "memory");
    return v;
}
__device__ __forceinline__ void sts32(uint32_t addr, float v) {
    asm volatile("st.shared.f32 [%0], %1;" ::"r"(addr), "f"(v) : "memory");
}
__device__ __forceinline__ float bf_lo(uint32_t v) { return __uint_as_float(v << 16); }
__device__ __forceinline__ float bf_hi(uint32_t v) { return __uint_as_float(v & 0xffff0000u); }
__device__ __forceinline__ uint32_t pack_bf16(float lo, float hi) {
    const __nv_bfloat162 p = __floats2bfloat162_rn(lo, hi);
    return *reinterpret_cast<const uint32_t*>(&p);
}
__device__ __forceinline__ uint32_t now_ns() {
    unsigned long long t;
    asm volatile("mov.u64 %0, %%globaltimer;" : "=l"(t));
    return (uint32_t)t;
}

__device__ __forceinline__ void wait_until(uint32_t t_start, uint32_t deadline) {
    unsigned n = 0;
    while (now_ns() - t_start < deadline && ++n < SPIN_LIMIT) {}
}

__device__ __forceinline__ uint32_t ll_pack(float v, uint32_t tag) {
    uint32_t w;
    asm("lop3.b32 %0, %1, 0xfffffffe, %2, 0xEA;" : "=r"(w) : "r"(__float_as_uint(v)), "r"(tag));
    return w;
}
__device__ __forceinline__ float ll_val(uint32_t w) { return __uint_as_float(w); }
__device__ __forceinline__ void ll_check(uint32_t& bad, uint32_t w, uint32_t tag) {
    asm("lop3.b32 %0, %1, %2, %0, 0xBE;" : "+r"(bad) : "r"(w), "r"(tag));
}
__device__ __forceinline__ float ex2(float v) {
    float r;
    asm("ex2.approx.ftz.f32 %0, %1;" : "=f"(r) : "f"(v));
    return r;
}
__device__ __forceinline__ float rcp(float v) {
    float r;
    asm("rcp.approx.ftz.f32 %0, %1;" : "=f"(r) : "f"(v));
    return r;
}
constexpr float LOG2E = 1.4426950408889634f;
__device__ __forceinline__ void ll_store(uint32_t* p, uint32_t w) {
    asm volatile("st.relaxed.gpu.global.b32 [%0], %1;" ::"l"(p), "r"(w) : "memory");
}
__device__ __forceinline__ uint32_t ll_ld(const uint32_t* p) {
    uint32_t v;
    asm volatile("ld.relaxed.gpu.global.b32 %0, [%1];" : "=r"(v) : "l"(p) : "memory");
    return v;
}
__device__ __forceinline__ uint2 ll_ld2(const uint32_t* p) {
    uint2 v;
    asm volatile("ld.relaxed.gpu.global.v2.b32 {%0,%1}, [%2];" : "=r"(v.x), "=r"(v.y) : "l"(p) : "memory");
    return v;
}
__device__ __forceinline__ uint4 ll_ld4(const uint32_t* p) {
    uint4 v;
    asm volatile("ld.relaxed.gpu.global.v4.b32 {%0,%1,%2,%3}, [%4];"
                 : "=r"(v.x), "=r"(v.y), "=r"(v.z), "=r"(v.w) : "l"(p) : "memory");
    return v;
}
template <int N>
__device__ __forceinline__ void ll_poll4(uint4 (&v)[N], const uint32_t* p, int stride, uint32_t tag) {
    unsigned n = 0;
#pragma unroll 1
    while (true) {
        uint32_t bad = 0;
#pragma unroll
        for (int i = 0; i < N; i++) v[i] = ll_ld4(p + i * stride);
#pragma unroll
        for (int i = 0; i < N; i++) { ll_check(bad, v[i].x, tag); ll_check(bad, v[i].y, tag); ll_check(bad, v[i].z, tag); ll_check(bad, v[i].w, tag); }
        if (__all_sync(0xffffffffu, (bad & 1u) == 0) || ++n > SPIN_LIMIT) break;
    }
}
__device__ __forceinline__ uint2 upper_halves(const uint4& v) {
    return make_uint2(__byte_perm(v.x, v.y, 0x7632), __byte_perm(v.z, v.w, 0x7632));
}
template <int N>
__device__ __forceinline__ float ll_poll_sum(const uint32_t* p, int stride, uint32_t tag) {
    uint32_t w[N];
    unsigned n = 0;
#pragma unroll 1
    while (true) {
        uint32_t bad = 0;
#pragma unroll
        for (int i = 0; i < N; i++) w[i] = ll_ld(p + i * stride);
#pragma unroll
        for (int i = 0; i < N; i++) ll_check(bad, w[i], tag);
        if ((bad & 1u) == 0 || ++n > SPIN_LIMIT) break;
    }
    float s = 0.f;
#pragma unroll
    for (int i = 0; i < N; i++) s += ll_val(w[i]);
    return s;
}
__device__ __forceinline__ float pick4(float a, float b, float c, float d, int j) {
    const float lo = (j & 1) ? b : a, hi = (j & 1) ? d : c;
    return (j & 2) ? hi : lo;
}
__device__ __forceinline__ float silu_f(float v) { return v * rcp(1.f + ex2(-LOG2E * v)); }

struct Params {
    const __nv_bfloat16* x;
    const __nv_bfloat16* k_win;
    __nv_bfloat16* out;
    uint32_t step, step_ffn, step_wo, step_ahead, step_start;
    uint32_t t_last, t_late;
    const char* w2;
    const char* wo;
};

__global__ void __launch_bounds__(N_THREADS, 1)
fused_decode_kernel(const Params prm,
                    const __grid_constant__ CUtensorMap tm_wq, const __grid_constant__ CUtensorMap tm_w1,
                    const __grid_constant__ CUtensorMap tm_w3, const __grid_constant__ CUtensorMap tm_k,
                    const __grid_constant__ CUtensorMap tm_v, const __grid_constant__ CUtensorMap tm_wo,
                    const __grid_constant__ CUtensorMap tm_w2, const __grid_constant__ CUtensorMap tm_wc) {
    extern __shared__ uint8_t smem_raw[];
    const uint32_t sb = (smem_u32(smem_raw) + 1023u) & ~1023u;
    uint8_t* sp = smem_raw + (sb - smem_u32(smem_raw));
    const uint32_t bar_full = sb + SM_BAR;
    const uint32_t bar_empty = bar_full + N_SLOT * 8;
    const uint32_t bar_t = bar_empty + N_SLOT * 8;
    const uint32_t go_k = bar_t + 12 * 8, go_s = go_k + 8, go_q = go_k + 16;
    const uint32_t go_b = go_k + 4 * 8;
    const uint32_t bar_s = go_b + 4 * 8;
    const uint32_t go_o = bar_s + 4 * 8;
    const uint32_t bar_q = go_o + 12 * 8;

    const int tid = threadIdx.x;
    const int cta = blockIdx.x;
    volatile uint32_t* t_first = reinterpret_cast<volatile uint32_t*>(sp + SM_BAR + 824);
    const __nv_bfloat16* k0 = prm.k_win + (uint64_t)blockIdx.x * (TILE_ROWS * D_HEAD);
    asm volatile("{ .reg .pred p; .reg .b64 a; setp.lt.u32 p, %1, %2; mad.wide.u32 a, %1, 32, %0; @p prefetch.global.L2 [a]; }"
                 ::"l"(k0), "r"(tid), "n"(TILE_BYTES / 32) : "memory");
    if (tid == N_CONS) {
        const uint32_t t_now = now_ns();
#pragma unroll
        for (int i = 0; i < N_PLAIN; i++) mbar_init(bar_full + (T_K + i) * 8, 1);
        asm volatile("fence.mbarrier_init.release.cluster;" ::: "memory");
        const uint64_t pol = stream_policy();
#pragma unroll
        for (int i = 0; i < N_PLAIN; i++) {
            mbar_expect_tx(bar_full + (T_K + i) * 8, TILE_BYTES);
            bulk_load(sb + SM_RING + (T_K + i) * TILE_BYTES, k0 + (size_t)i * SEQ * D_HEAD, TILE_BYTES, bar_full + (T_K + i) * 8, pol);
        }
        t_first[-1] = 0;
        prefetch_tmap(&tm_wq);
        *t_first = t_now;
#pragma unroll
        for (int i = 0; i < N_SLOT; i++)
            if (i < T_K || i >= T_K + N_PLAIN) mbar_init(bar_full + i * 8, 1);
        asm volatile("fence.mbarrier_init.release.cluster;" ::: "memory");
    }
    const int warp = __shfl_sync(0xffffffffu, tid >> 5, 0), lane = tid & 31;
    const int head = cta / SPLIT, r = cta % SPLIT;
    const int idx = cta >> 1, quad = (idx >> 2) - 2;
    const bool odd = cta & 1;
    const bool owner = !odd && quad >= 0 && quad % 3 != 2;
    const int own = (quad - quad / 3) * 4 + (idx & 3);

    int producer = warp == N_CONS_WARPS;
    asm volatile("" : "+r"(producer));
    if (producer) {
        __syncwarp();
        named_arrive(6, N_THREADS);
        if (elect_one()) {
            const uint64_t pol = stream_policy();
            const uint32_t t_start0 = *t_first;
            uint32_t t_start = t_start0;
            prefetch_tmap(&tm_w1); prefetch_tmap(&tm_w3); prefetch_tmap(&tm_k); prefetch_tmap(&tm_v); prefetch_tmap(&tm_wo);
            prefetch_tmap(&tm_w2); prefetch_tmap(&tm_wc);
            uint32_t deadline = 0;
            bool first = true;
#pragma unroll 1
            for (int t = 0; t <= T_W3; t++) {
                const bool q = t < T_W1;
                const CUtensorMap* tm = q ? &tm_wq : (t == T_W1 ? &tm_w1 : &tm_w3);
                const int c1 = (q ? head : cta / FF_GROUP) * 3;
                const int c2 = q ? r * ROWS_PER_CTA + t * TILE_ROWS : (cta % FF_GROUP) * FF_ROWS;
                const uint32_t dst = sb + SM_RING + (t == T_W3 ? T_W1 * TILE_BYTES + W13_BYTES : t * TILE_BYTES);
                const int rows = q ? SUB_ROWS : 8, pieces = q ? TILE_ROWS / SUB_ROWS : FF_ROWS / 8;
                mbar_expect_tx(bar_full + t * 8, q ? TILE_BYTES : W13_BYTES);
#pragma unroll 1
                for (int j = 0; j < pieces; j++) {
                    wait_until(t_start, deadline);
                    tma_3d(dst + j * rows * 384, tm, 0, c1, c2 + j * rows, bar_full + t * 8, pol);
                    deadline += q ? prm.step : prm.step_ffn;
                    if (first) { deadline += prm.step_start; first = false; }
                }
            }
            mbar_wait(bar_full + 7 * 8, 0);
            mbar_expect_tx(bar_full + (T_K + N_PLAIN) * 8, TILE_BYTES);
#pragma unroll 1
            for (int t = T_K + N_PLAIN; t < T_END; t++) {
                const int slot = t & (N_SLOT - 1), next = (t + 1) & (N_SLOT - 1);
                const uint32_t fb = bar_full + slot * 8, dst = sb + SM_RING + slot * TILE_BYTES;
                const CUtensorMap* tm = t >= T_V ? &tm_v : &tm_k;
                const int row = ((t - T_K) & (N_HEAD - 1)) * SEQ + (SEQ - WIN) + cta * TILE_ROWS;
                wait_until(t_start, deadline);
                tma_3d(dst, tm, 0, 0, row, fb, pol);
                deadline += prm.step;
                mbar_wait(bar_empty + next * 8, (((t + 1) >> 4) - 1) & 1);
                if (t + 1 < T_END) mbar_expect_tx(bar_full + next * 8, TILE_BYTES);
                wait_until(t_start, deadline);
                tma_3d(dst + SUB_ROWS * 384, tm, 0, 0, row + SUB_ROWS, fb, pol);
                deadline += prm.step;
                t_start = t_start0 - t_first[-1];
                const int u = max(t + 1 - INFLIGHT, 7);
                mbar_wait(bar_full + (u & (N_SLOT - 1)) * 8, (u >> 4) & 1);
            }
            if (odd) {
                constexpr int AHEAD_BYTES = AHEAD_ROWS * D_MODEL * 2;
                const char* w2 = prm.w2 + idx * AHEAD_BYTES;
                const char* wo = prm.wo + (idx - AHEAD_W2 * N_WO) * AHEAD_BYTES;
                mbar_wait(bar_empty + (N_SLOT - 1) * 8, 1);
#pragma unroll 1
                for (int n = 0; n < WO_ROUNDS; n++) {
                    const uint32_t dst = n < WO_WRAP ? TAIL_SLOT * TILE_BYTES + n * WO_BYTES : (n - WO_WRAP) * WO_BYTES;
                    wait_until(t_start, deadline);
                    tma_3d(sb + SM_RING + dst, &tm_wo, 0, (GROUP0 + n * N_WO + idx) * 8, 0, bar_t + n * 8, pol);
                    deadline += prm.step_wo;
                    if (n == WO_WRAP - 2) mbar_wait(bar_empty, 0);
                }
                deadline += AHEAD_LAG - prm.step_wo;
#pragma unroll 1
                for (int k = AHEAD_FROM; k < AHEAD_END; k++) {
                    wait_until(t_start, deadline);
                    asm volatile("cp.async.bulk.prefetch.L2.global [%0], %1;"
                                 ::"l"((k < AHEAD_W2 ? w2 : wo) + k * (N_WO * AHEAD_BYTES)), "n"(AHEAD_BYTES) : "memory");
                    deadline += prm.step_ahead;
                }
            }
            if (owner) {
#pragma unroll 1
                for (int k = 0; k < N_HEAD; k++) mbar_expect_tx(bar_q + k * 8, PIECE_BYTES);
                mbar_wait(bar_empty + (TAIL_SLOT + (N_PIECE * PIECE_BYTES - 1) / TILE_BYTES) * 8, 1);
                wait_until(t_start, prm.t_last + PIECE_LAG);
#pragma unroll 1
                for (int k = 0; k < N_PIECE; k++)
                    tma_3d(sb + SM_RING + TAIL_SLOT * TILE_BYTES + k * PIECE_BYTES, k < W2_PIECES ? &tm_w2 : &tm_wc, own * OWN_COLS,
                           (k < W2_PIECES ? k : k - W2_PIECES) * PIECE_ROWS, 0, k < N_HEAD ? bar_q + k * 8 : bar_t + (k - N_HEAD) * 8, pol);
            }
        }
        return;
    }

    if (tid == (N_CONS_WARPS + 1) * 32) {
#pragma unroll 1
        for (int i = 0; i < N_SLOT; i++) mbar_init(bar_empty + i * 8, V_WARPS);
        asm volatile("fence.mbarrier_init.release.cluster;" ::: "memory");
    }
    if (warp >= N_CONS_WARPS + 2 && warp < N_CONS_WARPS + 2 + N_AUX && lane == 0) {
        const uint32_t b0 = bar_t + (warp - (N_CONS_WARPS + 2)) * 17 * 8;
#pragma unroll 1
        for (int i = 0; i < 17; i++) mbar_init(b0 + i * 8, 1);
        asm volatile("fence.mbarrier_init.release.cluster;" ::: "memory");
        if (warp == N_CONS_WARPS + 2) {
#pragma unroll 1
            for (int k = 0; k < WO_ROUNDS; k++) mbar_expect_tx(bar_t + k * 8, odd ? WO_BYTES : PIECE_BYTES);
        }
    }
    __syncwarp();
    uint2 xin = make_uint2(0u, 0u);
    if (warp < 5) xin = *reinterpret_cast<const uint2*>(prm.x + tid * 4);
    volatile uint32_t* s_epoch = reinterpret_cast<volatile uint32_t*>(sp + SM_ML + 60);
    if (tid == 5 * 32) *s_epoch = ll_ld(&g_epoch);

    if (warp == N_CONS_WARPS + 1) {
        const int lc = lane & (OWN_COLS - 1);
        const int col = own * OWN_COLS + lc;
        uint32_t x_lo = 0;
        if (owner) x_lo = reinterpret_cast<const uint16_t*>(prm.x)[col];
        uint16_t* outp = reinterpret_cast<uint16_t*>(prm.out) + col;
        asm volatile("" : "+l"(outp));
        named_sync(6, N_THREADS);
        const uint32_t tag = (*s_epoch + 1u) & 1u;
        if (lane == 0) {
            ll_store(g_xt + cta, (*t_first & ~1u) | tag);
            mbar_arrive(bar_full + 7 * 8);
        }
        {
            const int c = lane < 24 ? lane >> 1 : 0;
            const uint32_t* xf = g_x1 + (cta / FF_GROUP) * FF_GROUP * X1_STRIDE + 192 + (lane & 1) * 192 +
                                 (cta % FF_GROUP) * FF_PER_CTA + c;
            mbar_wait(bar_full + FFN_TILE * 8, 0);
            const float mine = bf16r(ll_poll_sum<16>(xf, X1_STRIDE, tag));
            const float other = __shfl_xor_sync(0xffffffffu, mine, 1);
            const float hv = bf16r(bf16r(silu_f(mine)) * other);
            if (lane < 24 && !(lane & 1)) ll_store(g_xh + cta * FF_PER_CTA + c, __float_as_uint(hv) | tag);
        }
        bool pending = true;
#pragma unroll 1
        for (int b = 0; b < 4; b++) {
            mbar_wait(go_b + b * 8, 0);
            const int h = b * 8 + (lane & 7);
            uint2 v;
            unsigned n = 0;
#pragma unroll 1
            while (true) {
                uint32_t bad = 0;
                v = ll_ld2(g_xs + h * X2_STRIDE);
                ll_check(bad, v.x, tag); ll_check(bad, v.y, tag);
                if (__all_sync(0xffffffffu, (bad & 1u) == 0) || ++n > SPIN_LIMIT) break;
            }
            if (lane < 8) *reinterpret_cast<float2*>(sp + SM_S + h * 8) = make_float2(bf_hi(v.x), ll_val(v.y));
            __syncwarp();
            if (lane == 0) mbar_arrive(bar_s + b * 8);
            if (b == 2) {
                uint32_t due = t_first[0] - t_first[-1] + prm.t_late;
                int late = 0;
#pragma unroll 1
                for (int t = LATE_TILE; t < LATE_TILE + 4; t++) {
                    while (!mbar_try(bar_full + (t & (N_SLOT - 1)) * 8, (t >> 4) & 1) && (int)(now_ns() - due) < MAX_LATE) {}
                    late += min((int)(now_ns() - due), MAX_LATE);
                    due += 2 * prm.step;
                }
                if (lane == 0) ll_store(g_xl + cta, ((uint32_t)late & ~1u) | tag);
                if (!odd && idx < N_LATE) {
                    wait_until(due - MAX_LATE, MAX_LATE + LATE_LAG + late / 4);
                    uint4 w[1];
                    ll_poll4<1>(w, g_xl + lane * 4, 0, tag);
                    late = __reduce_add_sync(0xffffffffu, (int)(w[0].x + w[0].y + w[0].z + w[0].w)) / (4 * N_CTA);
                    late = min(max(late * LATE_GAIN / 8, 0), MAX_LATE);
                    if (lane < 8) ll_store(g_xm + idx * 32 + lane, ((uint32_t)late & ~1u) | tag);
                }
                mbar_wait(bar_full + (DELAY_TILE & (N_SLOT - 1)) * 8, (DELAY_TILE >> 4) & 1);
            }
            if (b >= 2 && pending) {
                const uint32_t w = ll_ld(g_xm + (idx % N_LATE) * 32);
                pending = (w ^ tag) & 1u;
                if (lane == 0 && !pending) t_first[-1] = t_first[-1] - w;
            }
        }
        if (owner) {
            uint32_t fin = sb + SM_FIN + lc * (FIN_STRIDE * 4);
            asm volatile("" : "+r"(fin));
            named_sync(5, N_CONS + 32);
            float fp[8];
#pragma unroll
            for (int i = 0; i < 8; i++) fp[i] = __uint_as_float(lds32(sb + SM_FIN + FIN_STRIDE * 64 + lc * 4 + i * 64));
            const float f = ((fp[0] + fp[1]) + (fp[2] + fp[3])) + ((fp[4] + fp[5]) + (fp[6] + fp[7]));
            const uint32_t g_lo = pack_bf16(silu_f(bf16r(f)), 0.f);
            sts32(fin + 72, __uint_as_float(g_lo));
            named_sync(14, N_AUX * 32 + 32);
            const float4 c = lds128(fin + 32), d = lds128(fin + 48);
            const float gathered = ((c.x + c.y) + (c.z + c.w)) + ((d.x + d.y) + (d.z + d.w));
            sts32(fin + 64, gathered);
            named_sync(12, N_CONS + 32);
            const float4 a = lds128(fin), b = lds128(fin + 16);
            const float sum = (((a.x + gathered) + a.y) + (a.z + a.w)) + ((b.x + b.y) + (b.z + b.w));
            uint32_t res;
            asm("{ .reg .b32 t; mul.rn.bf16x2 t, %1, %2; add.rn.bf16x2 %0, %3, t; }"
                : "=r"(res) : "r"(pack_bf16(sum, 0.f)), "r"(g_lo), "r"(x_lo));
            asm volatile("st.global.u16 [%0], %1;" ::"l"(outp), "h"((uint16_t)res) : "memory");
        }
        return;
    }
    if (warp >= N_CONS_WARPS + 2) {
        const int fw = warp - (N_CONS_WARPS + 2);
        named_sync(6, N_THREADS);
        const uint32_t epoch = *s_epoch, tag = (epoch + 1u) & 1u;
        mbar_wait(go_q, 0);
        if (fw == N_AUX - 1) {
            const uint4 v = ll_ld4(g_xt + lane * 4);
            uint32_t bad = 0;
            ll_check(bad, v.x, tag); ll_check(bad, v.y, tag); ll_check(bad, v.z, tag); ll_check(bad, v.w, tag);
            const uint32_t t0 = *t_first;
            int d = max(max((int)(t0 - v.x), (int)(t0 - v.y)), max((int)(t0 - v.z), (int)(t0 - v.w)));
#pragma unroll
            for (int o = 16; o > 0; o >>= 1) d = max(d, __shfl_xor_sync(0xffffffffu, d, o));
            if (__all_sync(0xffffffffu, (bad & 1u) == 0) && lane == 0) t_first[-1] = min(max(d, 0), MAX_SHIFT);
        }
        mbar_wait(bar_full + Q_TILE * 8, 0);
#pragma unroll 1
        for (int h = fw; h < N_HEAD; h += N_AUX) {
            uint4 v[2];
            ll_poll4<2>(v, g_xq + h * D_HEAD + (lane % 24) * 4, 96, tag);
            if (lane < 24) {
                *reinterpret_cast<uint2*>(sp + SM_Q + h * 384 + lane * 8) = upper_halves(v[0]);
                *reinterpret_cast<uint2*>(sp + SM_Q + h * 384 + 192 + lane * 8) = upper_halves(v[1]);
            }
            __syncwarp();
            if (lane == 0) mbar_arrive(bar_q + h * 8);
        }
        if (r == 0 && fw == N_AUX - 1) {
            mbar_wait(go_s, 0);
            const uint32_t* xm = g_x2 + (head * N_CTA + lane) * X2_STRIDE;
            uint2 ml[4];
            unsigned n = 0;
#pragma unroll 1
            while (true) {
                uint32_t bad = 0;
#pragma unroll
                for (int i = 0; i < 4; i++) ml[i] = ll_ld2(xm + i * 32 * X2_STRIDE);
#pragma unroll
                for (int i = 0; i < 4; i++) { ll_check(bad, ml[i].x, tag); ll_check(bad, ml[i].y, tag); }
                if (__all_sync(0xffffffffu, (bad & 1u) == 0) || ++n > SPIN_LIMIT) break;
            }
            float m = fmaxf(fmaxf(bf_hi(ml[0].x), bf_hi(ml[1].x)), fmaxf(bf_hi(ml[2].x), bf_hi(ml[3].x)));
#pragma unroll
            for (int o = 16; o > 0; o >>= 1) m = fmaxf(m, __shfl_xor_sync(0xffffffffu, m, o));
            float den = 0.f;
#pragma unroll
            for (int i = 0; i < 4; i++) den = fmaf(ex2((bf_hi(ml[i].x) - m) * LOG2E), ll_val(ml[i].y), den);
#pragma unroll
            for (int o = 16; o > 0; o >>= 1) den += __shfl_xor_sync(0xffffffffu, den, o);
            if (lane < X2_STRIDE) ll_store(g_xs + head * X2_STRIDE + lane, ll_pack(lane == 0 ? m : rcp(den), tag));
            if (cta == 0 && lane == 0) ll_store(&g_epoch, epoch + 1u);
        }
        if (owner) {
            mbar_wait(go_k, 0);
            uint4 v[3];
            ll_poll4<3>(v, g_xh + fw * 384 + lane * 4, 128, tag);
#pragma unroll
            for (int i = 0; i < 3; i++) *reinterpret_cast<uint2*>(sp + SM_H + (fw * 384 + i * 128 + lane * 4) * 2) = upper_halves(v[i]);
        }
#pragma unroll 1
        for (int s = fw; s < (odd ? WO_ROUNDS : XO_GROUPS); s += N_AUX) {
            const int grp = (odd ? GROUP0 : 0) + s * N_WO + idx;
            mbar_wait(go_o + s * 8, 0);
            if (grp >= (N_HEAD - 1) * 24) {
                const uint32_t c0 = clock();
                while ((uint32_t)clock() - c0 < (uint32_t)O_LAG) {}
            }
            uint4 v[8];
            ll_poll4<8>(v, g_x3 + grp * (N_CTA * 8) + lane * 4, 128, tag);
            float t0 = 0.f, t1 = 0.f, t2 = 0.f, t3 = 0.f;
#pragma unroll
            for (int i = 0; i < 8; i += 2) {
                t0 += ll_val(v[i].x) + ll_val(v[i + 1].x); t1 += ll_val(v[i].y) + ll_val(v[i + 1].y);
                t2 += ll_val(v[i].z) + ll_val(v[i + 1].z); t3 += ll_val(v[i].w) + ll_val(v[i + 1].w);
            }
            const bool u2 = lane & 2, u4 = lane & 4;
            const float a = (u2 ? t2 : t0) + __shfl_xor_sync(0xffffffffu, u2 ? t0 : t2, 2);
            const float b = (u2 ? t3 : t1) + __shfl_xor_sync(0xffffffffu, u2 ? t1 : t3, 2);
            float c = (u4 ? b : a) + __shfl_xor_sync(0xffffffffu, u4 ? a : b, 4);
            c += __shfl_xor_sync(0xffffffffu, c, 8);
            c += __shfl_xor_sync(0xffffffffu, c, 16);
            const int e = 4 * (lane & 1) + (lane & 2) + (lane >> 2);
            if (lane < 8) {
                if (odd) reinterpret_cast<uint16_t*>(sp + SM_O)[s * 8 + e] = (uint16_t)pack_bf16(c, 0.f);
                else ll_store(g_xo + grp * 8 + e, __float_as_uint(bf16r(c)) | tag);
            }
            if (s == fw + N_AUX) named_arrive(3, N_CONS + N_AUX * 32);
        }
        if (odd) named_arrive(13, N_CONS + N_AUX * 32);
        if (owner) {
            mbar_wait(go_o + XO_GROUPS * 8, 0);
            uint4 o[2];
            ll_poll4<2>(o, g_xo + fw * 128 + lane * 4, 512, tag);
#pragma unroll
            for (int i = 0; i < 2; i++)
                *reinterpret_cast<uint2*>(sp + SM_H + (D_FF + i * 512 + fw * 128 + lane * 4) * 2) = upper_halves(o[i]);
            named_arrive(4, N_AUX * 32 + N_CONS);
            const uint32_t* p = g_x5 + (own * N_WO + fw * (N_WO / N_AUX)) * OWN_COLS + lane;
            uint32_t dst = sb + SM_FIN + ((lane & 15) * FIN_STRIDE + 8 + fw * 2 + (lane >> 4)) * 4;
            uint32_t t_x5 = prm.t_last + X5_LAG;
            asm volatile("" : "+r"(dst), "+l"(p), "+r"(t_x5));
            mbar_wait(bar_q + X5_PIECE * 8, 1);
            wait_until(t_first[0] - t_first[-1], t_x5);
            unsigned n = 0;
#pragma unroll 1
            while (true) {
                uint32_t w[8];
#pragma unroll
                for (int i = 0; i < 8; i++) w[i] = ll_ld(p + i * 32);
                uint32_t bad[4];
#pragma unroll
                for (int i = 0; i < 4; i++)
                    asm("lop3.b32 %0, %1, %2, %3, 0x7E;" : "=r"(bad[i]) : "r"(w[2 * i]), "r"(w[2 * i + 1]), "r"(tag));
                const float c = ((ll_val(w[0]) + ll_val(w[1])) + (ll_val(w[2]) + ll_val(w[3]))) +
                                ((ll_val(w[4]) + ll_val(w[5])) + (ll_val(w[6]) + ll_val(w[7])));
                sts32(dst, c);
                if (__all_sync(0xffffffffu, !(((bad[0] | bad[1]) | (bad[2] | bad[3])) & 1u)) || ++n > SPIN_LIMIT) break;
            }
            named_arrive(14, N_AUX * 32 + 32);
        }
        return;
    }

    float* sml = reinterpret_cast<float*>(sp + SM_ML);
    if (warp < 5) {
        const uint2 u = xin;
        float s1 = (bf_lo(u.x) + bf_hi(u.x)) + (bf_lo(u.y) + bf_hi(u.y));
#pragma unroll
        for (int o = 16; o > 0; o >>= 1) s1 += __shfl_xor_sync(0xffffffffu, s1, o);
        if (lane == 0) sml[warp] = s1;
        named_sync(10, 160);
        const float mean = (((sml[0] + sml[1]) + (sml[2] + sml[3])) + sml[4]) * (1.f / D_MODEL);
        const float a = bf_lo(u.x) - mean, b = bf_hi(u.x) - mean, c = bf_lo(u.y) - mean, d = bf_hi(u.y) - mean;
        float s2 = fmaf(a, a, fmaf(b, b, fmaf(c, c, d * d)));
#pragma unroll
        for (int o = 16; o > 0; o >>= 1) s2 += __shfl_xor_sync(0xffffffffu, s2, o);
        if (lane == 0) sml[8 + warp] = s2;
        named_sync(10, 160);
        const float var = (((sml[8] + sml[9]) + (sml[10] + sml[11])) + sml[12]) * (1.f / D_MODEL);
        const float mean_b = bf16r(mean);
        float den;
        asm("sqrt.approx.f32 %0, %1;" : "=f"(den) : "f"(bf16r(bf16r(var) + 1e-5f)));
        const float inv = rcp(bf16r(den));
        const uint32_t d0 = pack_bf16(bf_lo(u.x) - mean_b, bf_hi(u.x) - mean_b);
        const uint32_t d1 = pack_bf16(bf_lo(u.y) - mean_b, bf_hi(u.y) - mean_b);
        *reinterpret_cast<uint2*>(sp + SM_XN + tid * 8) =
            make_uint2(pack_bf16(bf_lo(d0) * inv, bf_hi(d0) * inv), pack_bf16(bf_lo(d1) * inv, bf_hi(d1) * inv));
    }
    named_sync(6, N_THREADS);
    const uint32_t tag = (*s_epoch + 1u) & 1u;
    if (tid < Q_PER_CTA) ll_store(g_xq + cta * Q_PER_CTA + tid, tag ^ 1u);

    const int q4 = lane & 3, g8 = lane >> 2;
    const int rowT = (lane & 7) + ((lane >> 4) << 3), hiT = (lane >> 3) & 1;

    uint32_t* x1 = g_x1 + cta * X1_STRIDE + q4 * 8 + g8;
    if (warp < 6) {
        const uint32_t xn_addr = sb + SM_XN + (r * ROWS_PER_CTA + 2 * q4) * 2;
        const int line = 3 * rowT + (warp >> 1);
        const uint32_t o0 = (line * 128 + ((hiT ^ (line & 7)) << 4)) ^ ((warp & 1) << 6), o1 = o0 ^ 32;
        float acc[2][4] = {};
#pragma unroll 1
        for (int t = 0; t < 5; t++) {
            mbar_wait(bar_full + t * 8, 0);
            const uint32_t tb = sb + SM_RING + t * TILE_BYTES;
#pragma unroll
            for (int kk = 0; kk < 2; kk++) {
                const uint32_t b0 = lds32(xn_addr + (t * 32 + kk * 16) * 2);
                const uint32_t b1 = lds32(xn_addr + (t * 32 + kk * 16 + 8) * 2);
                uint32_t a[4];
                ldsm_x4_t(a, tb + kk * 6144 + o0);
                mma_bf16(acc[0], a, b0, b1);
                ldsm_x4_t(a, tb + kk * 6144 + o1);
                mma_bf16(acc[1], a, b0, b1);
            }
        }
        ll_store(x1 + warp * 32, ll_pack(pick4(acc[0][0], acc[0][2], acc[1][0], acc[1][2], q4), tag));
        mbar_wait(bar_full + T_W3 * 8, 0);
        named_sync(11, 192);
        if (tid < 5 * V_WARPS) mbar_arrive(bar_empty + (tid / V_WARPS) * 8);
        if (tid < Q_PER_CTA) {
            const float qv = ll_poll_sum<4>(g_x1 + head * SPLIT * X1_STRIDE + r * Q_PER_CTA + tid, X1_STRIDE, tag);
            ll_store(g_xq + cta * Q_PER_CTA + tid, __float_as_uint(bf16r(qv)) | tag);
        }
        __syncwarp();
        if (tid == 0) mbar_arrive(go_q);
    } else {
        float acc[12][4] = {};
        mbar_wait(bar_full + (T_W1 + warp - 6) * 8, 0);
        const uint32_t xf_addr = sb + SM_XN + ((cta % FF_GROUP) * FF_ROWS + 2 * q4) * 2;
        uint32_t ad[3];
#pragma unroll
        for (int j = 0; j < 3; j++)
            ad[j] = sb + SM_RING + T_W1 * TILE_BYTES + (warp - 6) * W13_BYTES + (3 * rowT + j) * 128 + ((hiT ^ ((3 * rowT + j) & 7)) << 4);
#pragma unroll 1
        for (int ks = 0; ks < 3; ks++) {
            const uint32_t b0 = lds32(xf_addr + ks * 32);
            uint32_t b1 = 0u, step = ks * 6144;
            if (ks < 2) b1 = lds32(xf_addr + ks * 32 + 16);
            else if (lane >= 16) step -= 8 * 384;
#pragma unroll
            for (int mt = 0; mt < 12; mt++) {
                uint32_t a[4];
                ldsm_x4_t(a, (ad[mt >> 2] + step) ^ ((mt & 3) << 5));
                mma_bf16(acc[mt], a, b0, b1);
            }
        }
#pragma unroll
        for (int i = 0; i < 6; i++)
            ll_store(x1 + 192 + (warp - 6) * 192 + i * 32,
                     ll_pack(pick4(acc[2 * i][0], acc[2 * i][2], acc[2 * i + 1][0], acc[2 * i + 1][2], q4), tag));
        named_sync(7, 64);
        if (tid >= 192 && tid < 192 + 3 * V_WARPS) mbar_arrive(bar_empty + (T_W1 + (tid - 192) / V_WARPS) * 8);
    }
    named_sync(1, N_CONS);

    {
        const int rowN = (lane & 7) + (((lane >> 3) & 1) << 3), hiN = lane >> 4;
#pragma unroll 1
        for (int h = warp; h < N_HEAD; h += N_CONS_WARPS) {
            const int t = T_K + h, slot = t & (N_SLOT - 1);
            mbar_wait(bar_q + h * 8, 0);
            mbar_wait(bar_full + slot * 8, (t >> 4) & 1);
            const uint32_t tb = sb + SM_RING + slot * TILE_BYTES;
            const int swz = h < N_PLAIN ? 0 : 7;
            float acc[2][2][4] = {};
#pragma unroll 1
            for (int j = 0; j < 3; j++) {
                const uint32_t oj = tb + (3 * rowN + j) * 128 + ((hiN ^ ((3 * rowN + j) & swz)) << 4);
                const uint32_t qa = sb + SM_Q + h * 384 + (j * 64 + 2 * q4) * 2;
#pragma unroll
                for (int k = 0; k < 4; k++) {
                    const uint32_t b0 = lds32(qa + k * 32), b1 = lds32(qa + k * 32 + 16);
                    uint32_t a[4];
                    ldsm_x4(a, oj ^ (k << 5));
                    mma_bf16(acc[0][k & 1], a, b0, b1);
                    ldsm_x4(a, (oj + 6144) ^ (k << 5));
                    mma_bf16(acc[1][k & 1], a, b0, b1);
                }
            }
            __syncwarp();
            if (lane < V_WARPS) mbar_arrive(bar_empty + slot * 8);
            const float raw = pick4(acc[0][0][0] + acc[0][1][0], acc[0][0][2] + acc[0][1][2],
                                    acc[1][0][0] + acc[1][1][0], acc[1][0][2] + acc[1][1][2], q4);
            const float sc = bf16r(bf16r(raw) * 0.07216878364870323f);
            float mw = sc;
#pragma unroll
            for (int o = 16; o > 0; o >>= 1) mw = fmaxf(mw, __shfl_xor_sync(0xffffffffu, mw, o));
            const float p = ex2((sc - mw) * LOG2E);
            reinterpret_cast<uint16_t*>(sp + SM_P)[h * 32 + q4 * 8 + g8] = (uint16_t)pack_bf16(p, 0.f);
            float lw = p;
#pragma unroll
            for (int o = 16; o > 0; o >>= 1) lw += __shfl_xor_sync(0xffffffffu, lw, o);
            if (lane < X2_STRIDE) ll_store(g_x2 + (h * N_CTA + cta) * X2_STRIDE + lane, ll_pack(lane == 0 ? mw : lw, tag));
            if (lane == 0) {
                reinterpret_cast<float*>(sp + SM_M)[h] = mw;
                if (h == head + S_DELAY) mbar_arrive(go_s);
                if (h >= 23 && (h & 7) == 7) mbar_arrive(go_b + ((h >> 3) - 2) * 8);
            }
        }
    }
    if (odd && q4 < 2) {
#pragma unroll
        for (int j = 0; j < 5; j++) ll_store(g_x5 + ((j * 8 + warp) * N_WO + idx) * OWN_COLS + q4 * 8 + g8, tag ^ 1u);
    }
    named_sync(1, N_CONS);
    if (tid == 0) mbar_arrive(go_k);

    if (warp < V_WARPS) {
        const int line = 3 * rowT + (warp >> 1);
        const uint32_t o0 = (line * 128 + ((hiT ^ (line & 7)) << 4)) ^ ((warp & 1) << 6), o1 = o0 ^ 32;
        uint32_t* x3 = g_x3 + ((warp * 4 + q4) * N_CTA + cta) * 8 + g8;
#pragma unroll
        for (int h = N_HEAD - O_RACING; h < N_HEAD; h++) ll_store(x3 + h * X3_HEAD, tag ^ 1u);
        int s_next = 0, h_next = ((odd ? GROUP0 : 0) + idx) / 24 + O_DELAY;
#pragma unroll 1
        for (int h = 0; h < N_HEAD; h++) {
            const int slot = (T_V + h) & (N_SLOT - 1);
            if ((h & 7) == 0) mbar_wait(bar_s + h, 0);
            const float2 ms = *reinterpret_cast<const float2*>(sp + SM_S + h * 8);
            const float scale = ex2((reinterpret_cast<const float*>(sp + SM_M)[h] - ms.x) * LOG2E) * ms.y;
            mbar_wait(bar_full + slot * 8, ((T_V + h) >> 4) & 1);
            const uint32_t tb = sb + SM_RING + slot * TILE_BYTES;
            const uint32_t pa = sb + SM_P + (h * 32 + 2 * q4) * 2;
            float oacc[2][2][4] = {};
#pragma unroll
            for (int kk = 0; kk < 2; kk++) {
                const uint32_t b0 = lds32(pa + kk * 32), b1 = lds32(pa + kk * 32 + 16);
                uint32_t a[4];
                ldsm_x4_t(a, tb + kk * 6144 + o0);
                mma_bf16(oacc[0][kk], a, b0, b1);
                ldsm_x4_t(a, tb + kk * 6144 + o1);
                mma_bf16(oacc[1][kk], a, b0, b1);
            }
            __syncwarp();
            if (lane == 0) mbar_arrive(bar_empty + slot * 8);
            const float v = pick4(oacc[0][0][0] + oacc[0][1][0], oacc[0][0][2] + oacc[0][1][2],
                                  oacc[1][0][0] + oacc[1][1][0], oacc[1][0][2] + oacc[1][1][2], q4);
            ll_store(x3 + h * X3_HEAD, ll_pack(v * scale, tag));
            if (tid == 0) {
                if (h == head + S_DELAY - N_HEAD) mbar_arrive(go_s);
                if (h == 7 || h == 21) mbar_arrive(go_b + (h == 7 ? 2 : 3) * 8);
                while (h == h_next) {
                    mbar_arrive(go_o + s_next * 8);
                    s_next++;
                    if (odd) h_next = s_next < WO_ROUNDS ? min((GROUP0 + s_next * N_WO + idx) / 24 + O_DELAY, N_HEAD - 1) : -1;
                    else h_next = s_next < XO_GROUPS ? (s_next * N_WO + idx) / 24 + O_DELAY : s_next == XO_GROUPS ? XO_TILE : -1;
                }
            }
        }
    }

    constexpr int STEPS = N_PIECE / N_CONS_WARPS, W2_STEPS = W2_PIECES / N_CONS_WARPS;
    uint32_t hb[STEPS][4][2];
    if (owner) {
        named_sync(4, N_AUX * 32 + N_CONS);
#pragma unroll
        for (int k = 0; k < STEPS; k++)
#pragma unroll
            for (int i = 0; i < 4; i++) {
                const uint32_t ha = sb + SM_H + ((k * N_CONS_WARPS + warp) * PIECE_ROWS + i * 16 + 2 * q4) * 2;
                hb[k][i][0] = lds32(ha);
                hb[k][i][1] = lds32(ha + 16);
            }
    }

    if (odd) {
        uint32_t* x5 = g_x5 + (warp * N_WO + idx) * OWN_COLS + (q4 & 1) * 8 + g8;
        asm volatile("" : "+l"(x5));
        named_sync(3, N_CONS + N_AUX * 32);
        float acc[5][4] = {};
        uint32_t wa = sb + SM_RING + TAIL_SLOT * TILE_BYTES + (lane >> 4) * 2048 + (warp >> 2) * 1024 + (lane & 7) * 128 +
                      (((((warp & 3) << 1) | hiT) ^ (lane & 7)) << 4);
        auto multiply = [&](int p) {
            const uint32_t b0 = lds32(sb + SM_O + (p * 8 + 2 * q4) * 2);
            mbar_wait(bar_t + p * 8, 0);
            uint32_t a0[4], a1[4], a2[2];
            ldsm_x4_t(a0, wa);
            ldsm_x4_t(a1, wa + 4096);
            ldsm_x2_t(a2, wa + 8192);
            mma_bf16_k8(acc[0], a0[0], a0[1], b0);
            mma_bf16_k8(acc[1], a0[2], a0[3], b0);
            mma_bf16_k8(acc[2], a1[0], a1[1], b0);
            mma_bf16_k8(acc[3], a1[2], a1[3], b0);
            mma_bf16_k8(acc[4], a2[0], a2[1], b0);
        };
#pragma unroll 1
        for (int p = 0; p < WO_ROUNDS - 1; p++) {
            if (p == 2 * N_AUX) named_sync(13, N_CONS + N_AUX * 32);
            multiply(p);
            wa += p == WO_WRAP - 1 ? -(TAIL_SLOT * TILE_BYTES + (WO_WRAP - 1) * WO_BYTES) : WO_BYTES;
        }
        multiply(WO_ROUNDS - 1);
#pragma unroll
        for (int j = 0; j < 5; j++) ll_store(x5 + j * 8 * N_WO * OWN_COLS, ll_pack(q4 & 1 ? acc[j][2] : acc[j][0], tag));
    }

    if (owner) {
        float acc[4][4] = {};
        const uint32_t wa = sb + SM_RING + TAIL_SLOT * TILE_BYTES + (warp * PIECE_ROWS + rowT) * 32 + ((hiT ^ ((lane >> 2) & 1)) << 4);
        uint32_t fin_f = sb + SM_FIN + (16 * FIN_STRIDE + warp * 16 + (q4 & 1) * 8 + g8) * 4;
        uint32_t fin_s = sb + SM_FIN + (((q4 & 1) * 8 + g8) * FIN_STRIDE + warp) * 4;
        uint32_t bar = bar_q + warp * 8;
        asm volatile("" : "+r"(fin_f), "+r"(fin_s), "+r"(bar));
#pragma unroll
        for (int k = 0; k < STEPS; k++) {
            if (k < N_HEAD / N_CONS_WARPS) mbar_wait(bar + k * N_CONS_WARPS * 8, 1);
            else mbar_wait(bar - (bar_q - bar_t), 0);
            uint32_t a[4][4];
#pragma unroll
            for (int i = 0; i < 4; i++) ldsm_x4_t(a[i], wa + k * N_CONS_WARPS * PIECE_BYTES + i * 512);
#pragma unroll
            for (int i = 0; i < 4; i++) mma_bf16(acc[i], a[i], hb[k][i][0], hb[k][i][1]);
            if (k == W2_STEPS - 1 || k == STEPS - 1) {
                const float part = q4 ? (acc[0][2] + acc[1][2]) + (acc[2][2] + acc[3][2]) : (acc[0][0] + acc[1][0]) + (acc[2][0] + acc[3][0]);
                if (q4 < 2) sts32(k < W2_STEPS ? fin_f : fin_s, part);
                named_arrive(k < W2_STEPS ? 5 : 12, N_CONS + 32);
#pragma unroll
                for (int i = 0; i < 4; i++) acc[0][i] = acc[1][i] = acc[2][i] = acc[3][i] = 0.f;
            }
        }
    }
    return;
}


typedef CUresult (*EncodeTiledFn)(CUtensorMap*, CUtensorMapDataType, cuuint32_t, void*, const cuuint64_t*,
                                  const cuuint64_t*, const cuuint32_t*, const cuuint32_t*, CUtensorMapInterleave,
                                  CUtensorMapSwizzle, CUtensorMapL2promotion, CUtensorMapFloatOOBfill);

void encode_map(EncodeTiledFn fn, CUtensorMap* m, const void* base, cuuint64_t d1, cuuint64_t d2, cuuint64_t s1,
                cuuint64_t s2, cuuint32_t b1, cuuint32_t b2) {
    const cuuint64_t dims[3] = {64, d1, d2};
    const cuuint64_t strides[2] = {s1, s2};
    const cuuint32_t box[3] = {64, b1, b2};
    const cuuint32_t estr[3] = {1, 1, 1};
    fn(m, CU_TENSOR_MAP_DATA_TYPE_BFLOAT16, 3, const_cast<void*>(base), dims, strides, box, estr,
       CU_TENSOR_MAP_INTERLEAVE_NONE, CU_TENSOR_MAP_SWIZZLE_128B, CU_TENSOR_MAP_L2_PROMOTION_NONE,
       CU_TENSOR_MAP_FLOAT_OOB_FILL_NONE);
}

}

extern "C" void kernel_launch(void* const* d_in, const int* in_sizes, int n_in, void* d_out, int out_size) {
    (void)in_sizes; (void)n_in; (void)out_size;
    static EncodeTiledFn encode = nullptr;
    static double pace_scale = 1.0;
    if (!encode) {
        int dev = 0, mem_khz = 0, bus_bits = 0;
        cudaGetDevice(&dev);
        cudaDeviceGetAttribute(&mem_khz, cudaDevAttrMemoryClockRate, dev);
        cudaDeviceGetAttribute(&bus_bits, cudaDevAttrGlobalMemoryBusWidth, dev);
        const double peak_gbs = 2.0 * mem_khz * 1e-6 * bus_bits / 8.0;
        if (peak_gbs > 0.0) pace_scale = PACE_REF_GBS / peak_gbs;
        void* fn = nullptr;
        cudaDriverEntryPointQueryResult qr;
        cudaGetDriverEntryPoint("cuTensorMapEncodeTiled", &fn, cudaEnableDefault, &qr);
        encode = reinterpret_cast<EncodeTiledFn>(fn);
        cudaFuncSetAttribute(fused_decode_kernel, cudaFuncAttributeMaxDynamicSharedMemorySize, SM_ALLOC);
    }
    CUtensorMap tm_k, tm_v, tm_wq, tm_w1, tm_w3, tm_wo, tm_w2, tm_wc;
    {
        const cuuint64_t dims[3] = {D_MODEL, D_FF, 1};
        const cuuint64_t strides[2] = {D_MODEL * 2, (cuuint64_t)D_MODEL * 2 * D_FF};
        const cuuint32_t box[3] = {OWN_COLS, PIECE_ROWS, 1};
        const cuuint32_t estr[3] = {1, 1, 1};
        encode(&tm_w2, CU_TENSOR_MAP_DATA_TYPE_BFLOAT16, 3, d_in[8], dims, strides, box, estr, CU_TENSOR_MAP_INTERLEAVE_NONE,
               CU_TENSOR_MAP_SWIZZLE_32B, CU_TENSOR_MAP_L2_PROMOTION_NONE, CU_TENSOR_MAP_FLOAT_OOB_FILL_NONE);
        encode(&tm_wc, CU_TENSOR_MAP_DATA_TYPE_BFLOAT16, 3, d_in[4], dims, strides, box, estr, CU_TENSOR_MAP_INTERLEAVE_NONE,
               CU_TENSOR_MAP_SWIZZLE_32B, CU_TENSOR_MAP_L2_PROMOTION_NONE, CU_TENSOR_MAP_FLOAT_OOB_FILL_NONE);
    }
    encode_map(encode, &tm_k, d_in[1], 3, (cuuint64_t)N_HEAD * SEQ, 128, D_HEAD * 2, 3, SUB_ROWS);
    encode_map(encode, &tm_v, d_in[2], 3, (cuuint64_t)N_HEAD * SEQ, 128, D_HEAD * 2, 3, SUB_ROWS);
    encode_map(encode, &tm_wq, d_in[3], N_HEAD * 3, D_MODEL, 128, N_HEAD * D_HEAD * 2, 3, SUB_ROWS);
    encode_map(encode, &tm_w1, d_in[6], D_FF / 64, D_MODEL, 128, D_FF * 2, 3, 8);
    encode_map(encode, &tm_w3, d_in[7], D_FF / 64, D_MODEL, 128, D_FF * 2, 3, 8);
    encode_map(encode, &tm_wo, d_in[4], N_HEAD * D_HEAD, D_MODEL / 64, D_MODEL * 2, 128, 8, 10);
    Params prm;
    prm.x = static_cast<const __nv_bfloat16*>(d_in[0]);
    prm.k_win = static_cast<const __nv_bfloat16*>(d_in[1]) + (size_t)(SEQ - WIN) * D_HEAD;
    prm.out = static_cast<__nv_bfloat16*>(d_out);
    auto step = [&](double pace, double bytes) { return (uint32_t)(pace * pace_scale * bytes / TILE_BYTES + 0.01); };
    prm.step = step(PACE, SUB_ROWS * 384);
    prm.step_ffn = step(PACE, 8 * 384);
    prm.step_wo = step(PACE_WO, WO_BYTES / 2);
    prm.step_start = (uint32_t)(PACE_START * pace_scale + 0.5);
    prm.step_ahead = step(PACE_AHEAD, AHEAD_ROWS * D_MODEL);
    const uint32_t t_k = prm.step_start + 2 * T_W1 * prm.step + 2 * (FF_ROWS / 8) * prm.step_ffn;
    prm.t_late = t_k + (2 * (LATE_TILE - T_K - N_PLAIN) + 1) * prm.step + LATE_NS;
    prm.t_last = t_k + 2 * (T_END - T_K - N_PLAIN) * prm.step + (WO_ROUNDS - 1) * prm.step_wo;
    prm.w2 = static_cast<const char*>(d_in[8]);
    prm.wo = static_cast<const char*>(d_in[4]);
    fused_decode_kernel<<<N_CTA, N_THREADS, SM_ALLOC, cudaStreamPerThread>>>(
        prm, tm_wq, tm_w1, tm_w3, tm_k, tm_v, tm_wo, tm_w2, tm_wc);
}
```

```cpp
#include <cuda_runtime.h>
#include <cuda_bf16.h>
#include <cuda.h>
#include <stdint.h>

namespace {

constexpr int D_MODEL = 640;
constexpr int N_HEAD = 32;
constexpr int D_HEAD = 192;
constexpr int SEQ = 32768;
constexpr int WIN = 4096;
constexpr int D_FF = 1536;

constexpr int SPLIT = 4;
constexpr int N_CTA = N_HEAD * SPLIT;
constexpr int TILE_ROWS = WIN / N_CTA;
constexpr int TILE_BYTES = TILE_ROWS * D_HEAD * 2;
constexpr int N_SLOT = 16;

constexpr int ROWS_PER_CTA = D_MODEL / SPLIT;
constexpr int FF_GROUP = 16;
constexpr int FF_ROWS = D_MODEL / FF_GROUP;
constexpr int FF_PER_CTA = D_FF / N_CTA;
constexpr int Q_PER_CTA = D_HEAD / SPLIT;

constexpr int OWN_COLS = 16;
constexpr int N_OWN = D_MODEL / OWN_COLS;
constexpr int XO_ROWS = 1024;
constexpr int PIECE_ROWS = 64;
constexpr int PIECE_BYTES = PIECE_ROWS * OWN_COLS * 2;
constexpr int W2_PIECES = D_FF / PIECE_ROWS, N_PIECE = W2_PIECES + XO_ROWS / PIECE_ROWS;
constexpr int N_WO = N_CTA / 2;
constexpr int GROUP0 = XO_ROWS / 8;
constexpr int WO_ROUNDS = (N_HEAD * D_HEAD / 8 - GROUP0) / N_WO;
constexpr int WO_BYTES = 8 * D_MODEL * 2;
constexpr int XO_GROUPS = GROUP0 / N_WO;
constexpr int AHEAD_ROWS = 4;
constexpr int AHEAD_FROM = 4, AHEAD_W2 = D_FF / (N_WO * AHEAD_ROWS), AHEAD_END = AHEAD_W2 + XO_ROWS / (N_WO * AHEAD_ROWS);

constexpr int T_W1 = 5, T_W3 = 6;
constexpr int T_K = 8;
constexpr int T_V = T_K + N_HEAD;
constexpr int T_END = T_V + N_HEAD;
constexpr int N_PLAIN = 2;

constexpr int W13_BYTES = FF_ROWS * 192 * 2;
constexpr int TAIL_SLOT = T_END % N_SLOT;
constexpr int WO_WRAP = 9;

constexpr int N_CONS_WARPS = 8;
constexpr int N_CONS = N_CONS_WARPS * 32;
constexpr int N_AUX = 4;
constexpr int N_THREADS = N_CONS + 64 + N_AUX * 32;

constexpr double PACE = 484, PACE_WO = 480, PACE_REF_GBS = 3352.32;
constexpr double PACE_START = 250;
constexpr int PIECE_LAG = 130, AHEAD_LAG = 640, X5_LAG = 1540;
constexpr double PACE_AHEAD = 490;
constexpr int INFLIGHT = 5;
constexpr int SUB_ROWS = 16;
constexpr int MAX_SHIFT = 400;
constexpr int LATE_TILE = 49, LATE_NS = 1205, LATE_GAIN = 10, MAX_LATE = 2000;
constexpr int N_LATE = 8;

constexpr int X1_STRIDE = 576;
constexpr int X2_STRIDE = 8;
constexpr int X3_HEAD = N_CTA * D_HEAD;
constexpr int FIN_STRIDE = 20;
constexpr int V_WARPS = 6;
constexpr int Q_TILE = 12;
constexpr int FFN_TILE = 15;
constexpr int S_DELAY = 12;
constexpr int O_DELAY = 4;
constexpr int O_RACING = 6;
constexpr int O_LAG = 700;
constexpr int XO_TILE = 18;
constexpr int X5_PIECE = 12;
constexpr int LATE_LAG = 300;
constexpr int DELAY_TILE = 57;

constexpr unsigned SPIN_LIMIT = 1u << 22;

constexpr int SM_RING = 0;
constexpr int SM_H = N_SLOT * TILE_BYTES;
constexpr int SM_BAR = SM_H + (D_FF + XO_ROWS) * 2;
constexpr int SM_XN = SM_BAR + 832;
constexpr int SM_Q = SM_XN + 1280;
constexpr int SM_O = SM_Q + N_HEAD * 384;
constexpr int SM_ML = SM_O + 192;
constexpr int SM_M = SM_ML + 64;
constexpr int SM_S = SM_M + 128;
constexpr int SM_FIN = SM_S + 256;
constexpr int SM_P = SM_FIN + 16 * FIN_STRIDE * 4 + 512;
constexpr int SM_ALLOC = SM_P + 2048 + 1024;
static_assert(SM_ALLOC <= 232448, "shared memory");

__device__ uint32_t g_epoch;
__device__ __align__(128) uint32_t g_x1[N_CTA * X1_STRIDE];
__device__ __align__(128) uint32_t g_xq[N_HEAD * D_HEAD];
__device__ __align__(128) uint32_t g_x2[N_HEAD * N_CTA * X2_STRIDE];
__device__ __align__(128) uint32_t g_xs[N_HEAD * X2_STRIDE];
__device__ __align__(128) uint32_t g_x3[N_HEAD * X3_HEAD];
__device__ __align__(128) uint32_t g_xh[D_FF];
__device__ __align__(128) uint32_t g_xt[N_CTA];
__device__ __align__(128) uint32_t g_xl[N_CTA];
__device__ __align__(128) uint32_t g_xm[N_LATE * 32];
__device__ __align__(128) uint32_t g_xo[XO_ROWS];
__device__ __align__(128) uint32_t g_x5[N_OWN * N_WO * OWN_COLS];

__device__ __forceinline__ uint32_t smem_u32(const void* p) { return (uint32_t)__cvta_generic_to_shared(p); }

__device__ __forceinline__ void mbar_init(uint32_t bar, uint32_t cnt) {
    asm volatile("mbarrier.init.shared::cta.b64 [%0], %1;" ::"r"(bar), "r"(cnt) : "memory");
}
__device__ __forceinline__ void mbar_expect_tx(uint32_t bar, uint32_t bytes) {
    asm volatile("mbarrier.arrive.expect_tx.shared::cta.b64 _, [%0], %1;" ::"r"(bar), "r"(bytes) : "memory");
}
__device__ __forceinline__ void mbar_arrive(uint32_t bar) {
    asm volatile("mbarrier.arrive.shared::cta.b64 _, [%0];" ::"r"(bar) : "memory");
}
__device__ __forceinline__ void mbar_wait(uint32_t bar, uint32_t parity) {
    asm volatile(
        "{\n.reg .pred p;\n.reg .u32 n;\n"
        "mov.u32 n, 0;\n"
        "WAIT_LOOP:\n"
        "mbarrier.try_wait.parity.shared::cta.b64 p, [%0], %1;\n"
        "add.u32 n, n, 1;\n"
        "setp.lt.and.u32 p, n, %2, !p;\n"
        "@p bra WAIT_LOOP;\n}"
        ::"r"(bar), "r"(parity), "n"(SPIN_LIMIT) : "memory");
}
__device__ __forceinline__ bool mbar_try(uint32_t bar, uint32_t parity) {
    uint32_t ok;
    asm volatile("{ .reg .pred p; mbarrier.try_wait.parity.shared::cta.b64 p, [%1], %2; selp.u32 %0, 1, 0, p; }"
                 : "=r"(ok) : "r"(bar), "r"(parity) : "memory");
    return ok;
}
__device__ __forceinline__ void named_sync(int id, int n) {
    asm volatile("bar.sync %0, %1;" ::"r"(id), "r"(n) : "memory");
}
__device__ __forceinline__ void named_arrive(int id, int n) {
    asm volatile("bar.arrive %0, %1;" ::"r"(id), "r"(n) : "memory");
}
__device__ __forceinline__ bool elect_one() {
    uint32_t pred = 0;
    asm volatile("{ .reg .pred p; elect.sync _|p, 0xffffffff; @p mov.u32 %0, 1; }" : "+r"(pred));
    return pred;
}
__device__ __forceinline__ uint64_t stream_policy() {
    uint64_t pol;
    asm volatile("createpolicy.fractional.L2::evict_first.b64 %0, 1.0;" : "=l"(pol));
    return pol;
}
__device__ __forceinline__ void bulk_load(uint32_t dst, const void* src, uint32_t bytes, uint32_t bar, uint64_t pol) {
    asm volatile("cp.async.bulk.shared::cluster.global.mbarrier::complete_tx::bytes.L2::cache_hint [%0], [%1], %2, [%3], %4;"
                 ::"r"(dst), "l"(src), "r"(bytes), "r"(bar), "l"(pol) : "memory");
}
__device__ __forceinline__ void tma_3d(uint32_t dst, const CUtensorMap* tm, int c0, int c1, int c2, uint32_t bar, uint64_t pol) {
    asm volatile("cp.async.bulk.tensor.3d.shared::cluster.global.mbarrier::complete_tx::bytes.L2::cache_hint [%0], [%1, {%3, %4, %5}], [%2], %6;"
                 ::"r"(dst), "l"(tm), "r"(bar), "r"(c0), "r"(c1), "r"(c2), "l"(pol) : "memory");
}
__device__ __forceinline__ void prefetch_tmap(const CUtensorMap* tm) {
    asm volatile("prefetch.tensormap [%0];" ::"l"(tm) : "memory");
}
__device__ __forceinline__ void ldsm_x4(uint32_t (&r)[4], uint32_t addr) {
    asm volatile("ldmatrix.sync.aligned.m8n8.x4.shared.b16 {%0,%1,%2,%3}, [%4];"
                 : "=r"(r[0]), "=r"(r[1]), "=r"(r[2]), "=r"(r[3]) : "r"(addr) : "memory");
}
__device__ __forceinline__ void ldsm_x4_t(uint32_t (&r)[4], uint32_t addr) {
    asm volatile("ldmatrix.sync.aligned.m8n8.x4.trans.shared.b16 {%0,%1,%2,%3}, [%4];"
                 : "=r"(r[0]), "=r"(r[1]), "=r"(r[2]), "=r"(r[3]) : "r"(addr) : "memory");
}
__device__ __forceinline__ void mma_bf16(float (&c)[4], const uint32_t (&a)[4], uint32_t b0, uint32_t b1) {
    asm volatile("mma.sync.aligned.m16n8k16.row.col.f32.bf16.bf16.f32 {%0,%1,%2,%3}, {%4,%5,%6,%7}, {%8,%9}, {%0,%1,%2,%3};"
                 : "+f"(c[0]), "+f"(c[1]), "+f"(c[2]), "+f"(c[3])
                 : "r"(a[0]), "r"(a[1]), "r"(a[2]), "r"(a[3]), "r"(b0), "r"(b1));
}
__device__ __forceinline__ void mma_bf16_k8(float (&c)[4], uint32_t a0, uint32_t a1, uint32_t b0) {
    asm volatile("mma.sync.aligned.m16n8k8.row.col.f32.bf16.bf16.f32 {%0,%1,%2,%3}, {%4,%5}, {%6}, {%0,%1,%2,%3};"
                 : "+f"(c[0]), "+f"(c[1]), "+f"(c[2]), "+f"(c[3]) : "r"(a0), "r"(a1), "r"(b0));
}
__device__ __forceinline__ void ldsm_x2_t(uint32_t (&r)[2], uint32_t addr) {
    asm volatile("ldmatrix.sync.aligned.m8n8.x2.trans.shared.b16 {%0,%1}, [%2];" : "=r"(r[0]), "=r"(r[1]) : "r"(addr) : "memory");
}
__device__ __forceinline__ float bf16r(float v) {
    uint32_t r;
    asm("cvt.rn.bf16x2.f32 %0, %1, %2;" : "=r"(r) : "f"(v), "f"(0.f));
    return __uint_as_float(r);
}
__device__ __forceinline__ uint32_t lds32(uint32_t addr) {
    uint32_t v;
    asm volatile("ld.shared.b32 %0, [%1];" : "=r"(v) : "r"(addr) : "memory");
    return v;
}
__device__ __forceinline__ float4 lds128(uint32_t addr) {
    float4 v;
    asm volatile("ld.shared.v4.f32 {%0,%1,%2,%3}, [%4];" : "=f"(v.x), "=f"(v.y), "=f"(v.z), "=f"(v.w) : "r"(addr) : "memory");
    return v;
}
__device__ __forceinline__ void sts32(uint32_t addr, float v) {
    asm volatile("st.shared.f32 [%0], %1;" ::"r"(addr), "f"(v) : "memory");
}
__device__ __forceinline__ float bf_lo(uint32_t v) { return __uint_as_float(v << 16); }
__device__ __forceinline__ float bf_hi(uint32_t v) { return __uint_as_float(v & 0xffff0000u); }
__device__ __forceinline__ uint32_t pack_bf16(float lo, float hi) {
    const __nv_bfloat162 p = __floats2bfloat162_rn(lo, hi);
    return *reinterpret_cast<const uint32_t*>(&p);
}
__device__ __forceinline__ uint32_t now_ns() {
    unsigned long long t;
    asm volatile("mov.u64 %0, %%globaltimer;" : "=l"(t));
    return (uint32_t)t;
}

__device__ __forceinline__ void wait_until(uint32_t t_start, uint32_t deadline) {
    while (now_ns() - t_start < deadline) {}
}

__device__ __forceinline__ uint32_t ll_pack(float v, uint32_t tag) {
    uint32_t w;
    asm("lop3.b32 %0, %1, 0xfffffffe, %2, 0xEA;" : "=r"(w) : "r"(__float_as_uint(v)), "r"(tag));
    return w;
}
__device__ __forceinline__ float ll_val(uint32_t w) { return __uint_as_float(w); }
__device__ __forceinline__ void ll_check(uint32_t& bad, uint32_t w, uint32_t tag) {
    asm("lop3.b32 %0, %1, %2, %0, 0xBE;" : "+r"(bad) : "r"(w), "r"(tag));
}
__device__ __forceinline__ float ex2(float v) {
    float r;
    asm("ex2.approx.ftz.f32 %0, %1;" : "=f"(r) : "f"(v));
    return r;
}
__device__ __forceinline__ float rcp(float v) {
    float r;
    asm("rcp.approx.ftz.f32 %0, %1;" : "=f"(r) : "f"(v));
    return r;
}
constexpr float LOG2E = 1.4426950408889634f;
__device__ __forceinline__ void ll_store(uint32_t* p, uint32_t w) {
    asm volatile("st.relaxed.gpu.global.b32 [%0], %1;" ::"l"(p), "r"(w) : "memory");
}
__device__ __forceinline__ uint32_t ll_ld(const uint32_t* p) {
    uint32_t v;
    asm volatile("ld.relaxed.gpu.global.b32 %0, [%1];" : "=r"(v) : "l"(p) : "memory");
    return v;
}
__device__ __forceinline__ uint2 ll_ld2(const uint32_t* p) {
    uint2 v;
    asm volatile("ld.relaxed.gpu.global.v2.b32 {%0,%1}, [%2];" : "=r"(v.x), "=r"(v.y) : "l"(p) : "memory");
    return v;
}
__device__ __forceinline__ uint4 ll_ld4(const uint32_t* p) {
    uint4 v;
    asm volatile("ld.relaxed.gpu.global.v4.b32 {%0,%1,%2,%3}, [%4];"
                 : "=r"(v.x), "=r"(v.y), "=r"(v.z), "=r"(v.w) : "l"(p) : "memory");
    return v;
}
template <int N>
__device__ __forceinline__ void ll_poll4(uint4 (&v)[N], const uint32_t* p, int stride, uint32_t tag) {
    unsigned n = 0;
#pragma unroll 1
    while (true) {
        uint32_t bad = 0;
#pragma unroll
        for (int i = 0; i < N; i++) v[i] = ll_ld4(p + i * stride);
#pragma unroll
        for (int i = 0; i < N; i++) { ll_check(bad, v[i].x, tag); ll_check(bad, v[i].y, tag); ll_check(bad, v[i].z, tag); ll_check(bad, v[i].w, tag); }
        if (__all_sync(0xffffffffu, (bad & 1u) == 0) || ++n > SPIN_LIMIT) break;
    }
}
__device__ __forceinline__ uint2 upper_halves(const uint4& v) {
    return make_uint2(__byte_perm(v.x, v.y, 0x7632), __byte_perm(v.z, v.w, 0x7632));
}
template <int N>
__device__ __forceinline__ float ll_poll_sum(const uint32_t* p, int stride, uint32_t tag) {
    uint32_t w[N];
    unsigned n = 0;
#pragma unroll 1
    while (true) {
        uint32_t bad = 0;
#pragma unroll
        for (int i = 0; i < N; i++) w[i] = ll_ld(p + i * stride);
#pragma unroll
        for (int i = 0; i < N; i++) ll_check(bad, w[i], tag);
        if ((bad & 1u) == 0 || ++n > SPIN_LIMIT) break;
    }
    float s = 0.f;
#pragma unroll
    for (int i = 0; i < N; i++) s += ll_val(w[i]);
    return s;
}
__device__ __forceinline__ float pick4(float a, float b, float c, float d, int j) {
    const float lo = (j & 1) ? b : a, hi = (j & 1) ? d : c;
    return (j & 2) ? hi : lo;
}
__device__ __forceinline__ float silu_f(float v) { return v * rcp(1.f + ex2(-LOG2E * v)); }

struct Params {
    const __nv_bfloat16* x;
    const __nv_bfloat16* k_win;
    __nv_bfloat16* out;
    uint32_t step, step_ffn, step_wo, step_ahead, step_start;
    uint32_t t_last, t_late;
    const char* w2;
    const char* wo;
};

__global__ void __launch_bounds__(N_THREADS, 1)
fused_decode_kernel(const Params prm,
                    const __grid_constant__ CUtensorMap tm_wq, const __grid_constant__ CUtensorMap tm_w1,
                    const __grid_constant__ CUtensorMap tm_w3, const __grid_constant__ CUtensorMap tm_k,
                    const __grid_constant__ CUtensorMap tm_v, const __grid_constant__ CUtensorMap tm_wo,
                    const __grid_constant__ CUtensorMap tm_w2, const __grid_constant__ CUtensorMap tm_wc) {
    extern __shared__ uint8_t smem_raw[];
    const uint32_t sb = (smem_u32(smem_raw) + 1023u) & ~1023u;
    uint8_t* sp = smem_raw + (sb - smem_u32(smem_raw));
    const uint32_t bar_full = sb + SM_BAR;
    const uint32_t bar_empty = bar_full + N_SLOT * 8;
    const uint32_t bar_t = bar_empty + N_SLOT * 8;
    const uint32_t go_k = bar_t + 12 * 8, go_s = go_k + 8, go_q = go_k + 16;
    const uint32_t go_b = go_k + 4 * 8;
    const uint32_t bar_s = go_b + 4 * 8;
    const uint32_t go_o = bar_s + 4 * 8;
    const uint32_t bar_q = go_o + 12 * 8;

    const int tid = threadIdx.x;
    const int cta = blockIdx.x;
    volatile uint32_t* t_first = reinterpret_cast<volatile uint32_t*>(sp + SM_BAR + 824);
    const __nv_bfloat16* k0 = prm.k_win + (uint64_t)blockIdx.x * (TILE_ROWS * D_HEAD);
    asm volatile("{ .reg .pred p; .reg .b64 a; setp.lt.u32 p, %1, %2; mad.wide.u32 a, %1, 32, %0; @p prefetch.global.L2 [a]; }"
                 ::"l"(k0), "r"(tid), "n"(TILE_BYTES / 32) : "memory");
    if (tid == N_CONS) {
        const uint32_t t_now = now_ns();
#pragma unroll
        for (int i = 0; i < N_PLAIN; i++) mbar_init(bar_full + (T_K + i) * 8, 1);
        asm volatile("fence.mbarrier_init.release.cluster;" ::: "memory");
        const uint64_t pol = stream_policy();
#pragma unroll
        for (int i = 0; i < N_PLAIN; i++) {
            mbar_expect_tx(bar_full + (T_K + i) * 8, TILE_BYTES);
            bulk_load(sb + SM_RING + (T_K + i) * TILE_BYTES, k0 + (size_t)i * SEQ * D_HEAD, TILE_BYTES, bar_full + (T_K + i) * 8, pol);
        }
        t_first[-1] = 0;
        prefetch_tmap(&tm_wq);
        *t_first = t_now;
#pragma unroll
        for (int i = 0; i < N_SLOT; i++)
            if (i < T_K || i >= T_K + N_PLAIN) mbar_init(bar_full + i * 8, 1);
        asm volatile("fence.mbarrier_init.release.cluster;" ::: "memory");
    }
    const int warp = __shfl_sync(0xffffffffu, tid >> 5, 0), lane = tid & 31;
    const int head = cta / SPLIT, r = cta % SPLIT;
    const int idx = cta >> 1, blk = idx >> 3;
    const bool odd = cta & 1;
    const bool owner = !odd && ((idx & 4) || blk == 3 || blk == 6);
    const int own = (idx & 4 ? blk : blk == 3 ? 8 : 9) * 4 + (idx & 3);

    int producer = warp == N_CONS_WARPS;
    asm volatile("" : "+r"(producer));
    if (producer) {
        __syncwarp();
        named_arrive(6, N_THREADS);
        if (elect_one()) {
            const uint64_t pol = stream_policy();
            const uint32_t t_start0 = *t_first;
            uint32_t t_start = t_start0;
            prefetch_tmap(&tm_w1); prefetch_tmap(&tm_w3); prefetch_tmap(&tm_k); prefetch_tmap(&tm_v); prefetch_tmap(&tm_wo);
            prefetch_tmap(&tm_w2); prefetch_tmap(&tm_wc);
            uint32_t deadline = 0;
            bool first = true;
#pragma unroll 1
            for (int t = 0; t <= T_W3; t++) {
                const bool q = t < T_W1;
                const CUtensorMap* tm = q ? &tm_wq : (t == T_W1 ? &tm_w1 : &tm_w3);
                const int c1 = (q ? head : cta / FF_GROUP) * 3;
                const int c2 = q ? r * ROWS_PER_CTA + t * TILE_ROWS : (cta % FF_GROUP) * FF_ROWS;
                const uint32_t dst = sb + SM_RING + (t == T_W3 ? T_W1 * TILE_BYTES + W13_BYTES : t * TILE_BYTES);
                const int rows = q ? SUB_ROWS : 8, pieces = q ? TILE_ROWS / SUB_ROWS : FF_ROWS / 8;
                mbar_expect_tx(bar_full + t * 8, q ? TILE_BYTES : W13_BYTES);
#pragma unroll 1
                for (int j = 0; j < pieces; j++) {
                    wait_until(t_start, deadline);
                    tma_3d(dst + j * rows * 384, tm, 0, c1, c2 + j * rows, bar_full + t * 8, pol);
                    deadline += q ? prm.step : prm.step_ffn;
                    if (first) { deadline += prm.step_start; first = false; }
                }
            }
            mbar_wait(bar_full + 7 * 8, 0);
            mbar_expect_tx(bar_full + (T_K + N_PLAIN) * 8, TILE_BYTES);
#pragma unroll 1
            for (int t = T_K + N_PLAIN; t < T_END; t++) {
                const int slot = t & (N_SLOT - 1), next = (t + 1) & (N_SLOT - 1);
                const uint32_t fb = bar_full + slot * 8, dst = sb + SM_RING + slot * TILE_BYTES;
                const CUtensorMap* tm = t >= T_V ? &tm_v : &tm_k;
                const int row = ((t - T_K) & (N_HEAD - 1)) * SEQ + (SEQ - WIN) + cta * TILE_ROWS;
                wait_until(t_start, deadline);
                tma_3d(dst, tm, 0, 0, row, fb, pol);
                deadline += prm.step;
                mbar_wait(bar_empty + next * 8, (((t + 1) >> 4) - 1) & 1);
                if (t + 1 < T_END) mbar_expect_tx(bar_full + next * 8, TILE_BYTES);
                wait_until(t_start, deadline);
                tma_3d(dst + SUB_ROWS * 384, tm, 0, 0, row + SUB_ROWS, fb, pol);
                deadline += prm.step;
                t_start = t_start0 - t_first[-1];
                const int u = max(t + 1 - INFLIGHT, 7);
                mbar_wait(bar_full + (u & (N_SLOT - 1)) * 8, (u >> 4) & 1);
            }
            if (odd) {
                constexpr int AHEAD_BYTES = AHEAD_ROWS * D_MODEL * 2;
                const char* w2 = prm.w2 + idx * AHEAD_BYTES;
                const char* wo = prm.wo + (idx - AHEAD_W2 * N_WO) * AHEAD_BYTES;
                mbar_wait(bar_empty + (N_SLOT - 1) * 8, 1);
#pragma unroll 1
                for (int n = 0; n < WO_ROUNDS; n++) {
                    const uint32_t dst = n < WO_WRAP ? TAIL_SLOT * TILE_BYTES + n * WO_BYTES : (n - WO_WRAP) * WO_BYTES;
                    wait_until(t_start, deadline);
                    tma_3d(sb + SM_RING + dst, &tm_wo, 0, (GROUP0 + n * N_WO + idx) * 8, 0, bar_t + n * 8, pol);
                    deadline += prm.step_wo;
                    if (n == WO_WRAP - 2) mbar_wait(bar_empty, 0);
                }
                deadline += AHEAD_LAG - prm.step_wo;
#pragma unroll 1
                for (int k = AHEAD_FROM; k < AHEAD_END; k++) {
                    wait_until(t_start, deadline);
                    asm volatile("cp.async.bulk.prefetch.L2.global [%0], %1;"
                                 ::"l"((k < AHEAD_W2 ? w2 : wo) + k * (N_WO * AHEAD_BYTES)), "n"(AHEAD_BYTES) : "memory");
                    deadline += prm.step_ahead;
                }
            }
            if (owner) {
#pragma unroll 1
                for (int k = 0; k < N_HEAD; k++) mbar_expect_tx(bar_q + k * 8, PIECE_BYTES);
                mbar_wait(bar_empty + (TAIL_SLOT + (N_PIECE * PIECE_BYTES - 1) / TILE_BYTES) * 8, 1);
                wait_until(t_start, prm.t_last + PIECE_LAG);
#pragma unroll 1
                for (int k = 0; k < N_PIECE; k++)
                    tma_3d(sb + SM_RING + TAIL_SLOT * TILE_BYTES + k * PIECE_BYTES, k < W2_PIECES ? &tm_w2 : &tm_wc, own * OWN_COLS,
                           (k < W2_PIECES ? k : k - W2_PIECES) * PIECE_ROWS, 0, k < N_HEAD ? bar_q + k * 8 : bar_t + (k - N_HEAD) * 8, pol);
            }
        }
        return;
    }

    if (tid == (N_CONS_WARPS + 1) * 32) {
#pragma unroll 1
        for (int i = 0; i < N_SLOT; i++) mbar_init(bar_empty + i * 8, V_WARPS);
        asm volatile("fence.mbarrier_init.release.cluster;" ::: "memory");
    }
    if (warp >= N_CONS_WARPS + 2 && warp < N_CONS_WARPS + 2 + N_AUX && lane == 0) {
        const uint32_t b0 = bar_t + (warp - (N_CONS_WARPS + 2)) * 17 * 8;
#pragma unroll 1
        for (int i = 0; i < 17; i++) mbar_init(b0 + i * 8, 1);
        asm volatile("fence.mbarrier_init.release.cluster;" ::: "memory");
        if (warp == N_CONS_WARPS + 2) {
#pragma unroll 1
            for (int k = 0; k < WO_ROUNDS; k++) mbar_expect_tx(bar_t + k * 8, odd ? WO_BYTES : PIECE_BYTES);
        }
    }
    __syncwarp();
    uint2 xin = make_uint2(0u, 0u);
    if (warp < 5) xin = *reinterpret_cast<const uint2*>(prm.x + tid * 4);
    volatile uint32_t* s_epoch = reinterpret_cast<volatile uint32_t*>(sp + SM_ML + 60);
    if (tid == 5 * 32) *s_epoch = ll_ld(&g_epoch);

    if (warp == N_CONS_WARPS + 1) {
        const int lc = lane & (OWN_COLS - 1);
        const int col = own * OWN_COLS + lc;
        uint32_t x_lo = 0;
        if (owner) x_lo = reinterpret_cast<const uint16_t*>(prm.x)[col];
        uint16_t* outp = reinterpret_cast<uint16_t*>(prm.out) + col;
        asm volatile("" : "+l"(outp));
        named_sync(6, N_THREADS);
        const uint32_t tag = (*s_epoch + 1u) & 1u;
        if (lane == 0) {
            ll_store(g_xt + cta, (*t_first & ~1u) | tag);
            mbar_arrive(bar_full + 7 * 8);
        }
        {
            const int c = lane < 24 ? lane >> 1 : 0;
            const uint32_t* xf = g_x1 + (cta / FF_GROUP) * FF_GROUP * X1_STRIDE + 192 + (lane & 1) * 192 +
                                 (cta % FF_GROUP) * FF_PER_CTA + c;
            mbar_wait(bar_full + FFN_TILE * 8, 0);
            const float mine = bf16r(ll_poll_sum<16>(xf, X1_STRIDE, tag));
            const float other = __shfl_xor_sync(0xffffffffu, mine, 1);
            const float hv = bf16r(bf16r(silu_f(mine)) * other);
            if (lane < 24 && !(lane & 1)) ll_store(g_xh + cta * FF_PER_CTA + c, __float_as_uint(hv) | tag);
        }
        bool pending = true;
#pragma unroll 1
        for (int b = 0; b < 4; b++) {
            mbar_wait(go_b + b * 8, 0);
            const int h = b * 8 + (lane & 7);
            uint2 v;
            unsigned n = 0;
#pragma unroll 1
            while (true) {
                uint32_t bad = 0;
                v = ll_ld2(g_xs + h * X2_STRIDE);
                ll_check(bad, v.x, tag); ll_check(bad, v.y, tag);
                if (__all_sync(0xffffffffu, (bad & 1u) == 0) || ++n > SPIN_LIMIT) break;
            }
            if (lane < 8) *reinterpret_cast<float2*>(sp + SM_S + h * 8) = make_float2(bf_hi(v.x), ll_val(v.y));
            __syncwarp();
            if (lane == 0) mbar_arrive(bar_s + b * 8);
            if (b == 2) {
                uint32_t due = t_first[0] - t_first[-1] + prm.t_late;
                int late = 0;
#pragma unroll 1
                for (int t = LATE_TILE; t < LATE_TILE + 4; t++) {
                    while (!mbar_try(bar_full + (t & (N_SLOT - 1)) * 8, (t >> 4) & 1) && (int)(now_ns() - due) < MAX_LATE) {}
                    late += min((int)(now_ns() - due), MAX_LATE);
                    due += 2 * prm.step;
                }
                if (lane == 0) ll_store(g_xl + cta, ((uint32_t)late & ~1u) | tag);
                if (!odd && !owner && blk < N_LATE / 4) {
                    wait_until(due - MAX_LATE, MAX_LATE + LATE_LAG + late / 4);
                    uint4 w[1];
                    ll_poll4<1>(w, g_xl + lane * 4, 0, tag);
                    late = __reduce_add_sync(0xffffffffu, (int)(w[0].x + w[0].y + w[0].z + w[0].w)) / (4 * N_CTA);
                    late = min(max(late * LATE_GAIN / 8, 0), MAX_LATE);
                    if (lane < 8) ll_store(g_xm + (blk * 4 + (idx & 3)) * 32 + lane, ((uint32_t)late & ~1u) | tag);
                }
                mbar_wait(bar_full + (DELAY_TILE & (N_SLOT - 1)) * 8, (DELAY_TILE >> 4) & 1);
            }
            if (b >= 2 && pending) {
                const uint32_t w = ll_ld(g_xm + (idx % N_LATE) * 32);
                pending = (w ^ tag) & 1u;
                if (lane == 0 && !pending) t_first[-1] = t_first[-1] - w;
            }
        }
        if (owner) {
            uint32_t fin = sb + SM_FIN + lc * (FIN_STRIDE * 4);
            asm volatile("" : "+r"(fin));
            named_sync(5, N_CONS + 32);
            float fp[8];
#pragma unroll
            for (int i = 0; i < 8; i++) fp[i] = __uint_as_float(lds32(sb + SM_FIN + FIN_STRIDE * 64 + lc * 4 + i * 64));
            const float f = ((fp[0] + fp[1]) + (fp[2] + fp[3])) + ((fp[4] + fp[5]) + (fp[6] + fp[7]));
            const uint32_t g_lo = pack_bf16(silu_f(bf16r(f)), 0.f);
            sts32(fin + 72, __uint_as_float(g_lo));
            named_sync(14, N_AUX * 32 + 32);
            const float4 c = lds128(fin + 32), d = lds128(fin + 48);
            const float gathered = ((c.x + c.y) + (c.z + c.w)) + ((d.x + d.y) + (d.z + d.w));
            sts32(fin + 64, gathered);
            named_sync(12, N_CONS + 32);
            const float4 a = lds128(fin), b = lds128(fin + 16);
            const float sum = (((a.x + gathered) + a.y) + (a.z + a.w)) + ((b.x + b.y) + (b.z + b.w));
            uint32_t res;
            asm("{ .reg .b32 t; mul.rn.bf16x2 t, %1, %2; add.rn.bf16x2 %0, %3, t; }"
                : "=r"(res) : "r"(pack_bf16(sum, 0.f)), "r"(g_lo), "r"(x_lo));
            asm volatile("st.global.u16 [%0], %1;" ::"l"(outp), "h"((uint16_t)res) : "memory");
        }
        return;
    }
    if (warp >= N_CONS_WARPS + 2) {
        const int fw = warp - (N_CONS_WARPS + 2);
        named_sync(6, N_THREADS);
        const uint32_t epoch = *s_epoch, tag = (epoch + 1u) & 1u;
        mbar_wait(go_q, 0);
        if (fw == N_AUX - 1) {
            const uint4 v = ll_ld4(g_xt + lane * 4);
            uint32_t bad = 0;
            ll_check(bad, v.x, tag); ll_check(bad, v.y, tag); ll_check(bad, v.z, tag); ll_check(bad, v.w, tag);
            const uint32_t t0 = *t_first;
            int d = max(max((int)(t0 - v.x), (int)(t0 - v.y)), max((int)(t0 - v.z), (int)(t0 - v.w)));
#pragma unroll
            for (int o = 16; o > 0; o >>= 1) d = max(d, __shfl_xor_sync(0xffffffffu, d, o));
            if (__all_sync(0xffffffffu, (bad & 1u) == 0) && lane == 0) t_first[-1] = min(max(d, 0), MAX_SHIFT);
        }
        mbar_wait(bar_full + Q_TILE * 8, 0);
#pragma unroll 1
        for (int h = fw; h < N_HEAD; h += N_AUX) {
            uint4 v[2];
            ll_poll4<2>(v, g_xq + h * D_HEAD + (lane % 24) * 4, 96, tag);
            if (lane < 24) {
                *reinterpret_cast<uint2*>(sp + SM_Q + h * 384 + lane * 8) = upper_halves(v[0]);
                *reinterpret_cast<uint2*>(sp + SM_Q + h * 384 + 192 + lane * 8) = upper_halves(v[1]);
            }
            __syncwarp();
            if (lane == 0) mbar_arrive(bar_q + h * 8);
        }
        if (r == 0 && fw == N_AUX - 1) {
            mbar_wait(go_s, 0);
            const uint32_t* xm = g_x2 + (head * N_CTA + lane) * X2_STRIDE;
            uint2 ml[4];
            unsigned n = 0;
#pragma unroll 1
            while (true) {
                uint32_t bad = 0;
#pragma unroll
                for (int i = 0; i < 4; i++) ml[i] = ll_ld2(xm + i * 32 * X2_STRIDE);
#pragma unroll
                for (int i = 0; i < 4; i++) { ll_check(bad, ml[i].x, tag); ll_check(bad, ml[i].y, tag); }
                if (__all_sync(0xffffffffu, (bad & 1u) == 0) || ++n > SPIN_LIMIT) break;
            }
            float m = fmaxf(fmaxf(bf_hi(ml[0].x), bf_hi(ml[1].x)), fmaxf(bf_hi(ml[2].x), bf_hi(ml[3].x)));
#pragma unroll
            for (int o = 16; o > 0; o >>= 1) m = fmaxf(m, __shfl_xor_sync(0xffffffffu, m, o));
            float den = 0.f;
#pragma unroll
            for (int i = 0; i < 4; i++) den = fmaf(ex2((bf_hi(ml[i].x) - m) * LOG2E), ll_val(ml[i].y), den);
#pragma unroll
            for (int o = 16; o > 0; o >>= 1) den += __shfl_xor_sync(0xffffffffu, den, o);
            if (lane < X2_STRIDE) ll_store(g_xs + head * X2_STRIDE + lane, ll_pack(lane == 0 ? m : rcp(den), tag));
            if (cta == 0 && lane == 0) ll_store(&g_epoch, epoch + 1u);
        }
        if (owner) {
            mbar_wait(go_k, 0);
            uint4 v[3];
            ll_poll4<3>(v, g_xh + fw * 384 + lane * 4, 128, tag);
#pragma unroll
            for (int i = 0; i < 3; i++) *reinterpret_cast<uint2*>(sp + SM_H + (fw * 384 + i * 128 + lane * 4) * 2) = upper_halves(v[i]);
        }
#pragma unroll 1
        for (int s = fw; s < (odd ? WO_ROUNDS : XO_GROUPS); s += N_AUX) {
            const int grp = (odd ? GROUP0 : 0) + s * N_WO + idx;
            mbar_wait(go_o + s * 8, 0);
            if (grp >= (N_HEAD - 1) * 24) {
                const uint32_t c0 = clock();
                while ((uint32_t)clock() - c0 < (uint32_t)O_LAG) {}
            }
            uint4 v[8];
            ll_poll4<8>(v, g_x3 + grp * (N_CTA * 8) + lane * 4, 128, tag);
            float t0 = 0.f, t1 = 0.f, t2 = 0.f, t3 = 0.f;
#pragma unroll
            for (int i = 0; i < 8; i += 2) {
                t0 += ll_val(v[i].x) + ll_val(v[i + 1].x); t1 += ll_val(v[i].y) + ll_val(v[i + 1].y);
                t2 += ll_val(v[i].z) + ll_val(v[i + 1].z); t3 += ll_val(v[i].w) + ll_val(v[i + 1].w);
            }
            const bool u2 = lane & 2, u4 = lane & 4;
            const float a = (u2 ? t2 : t0) + __shfl_xor_sync(0xffffffffu, u2 ? t0 : t2, 2);
            const float b = (u2 ? t3 : t1) + __shfl_xor_sync(0xffffffffu, u2 ? t1 : t3, 2);
            float c = (u4 ? b : a) + __shfl_xor_sync(0xffffffffu, u4 ? a : b, 4);
            c += __shfl_xor_sync(0xffffffffu, c, 8);
            c += __shfl_xor_sync(0xffffffffu, c, 16);
            const int e = 4 * (lane & 1) + (lane & 2) + (lane >> 2);
            if (lane < 8) {
                if (odd) reinterpret_cast<uint16_t*>(sp + SM_O)[s * 8 + e] = (uint16_t)pack_bf16(c, 0.f);
                else ll_store(g_xo + grp * 8 + e, __float_as_uint(bf16r(c)) | tag);
            }
            if (s == fw + N_AUX) named_arrive(3, N_CONS + N_AUX * 32);
        }
        if (odd) named_arrive(13, N_CONS + N_AUX * 32);
        if (owner) {
            mbar_wait(go_o + XO_GROUPS * 8, 0);
            uint4 o[2];
            ll_poll4<2>(o, g_xo + fw * 128 + lane * 4, 512, tag);
#pragma unroll
            for (int i = 0; i < 2; i++)
                *reinterpret_cast<uint2*>(sp + SM_H + (D_FF + i * 512 + fw * 128 + lane * 4) * 2) = upper_halves(o[i]);
            named_arrive(4, N_AUX * 32 + N_CONS);
            const uint32_t* p = g_x5 + (own * N_WO + fw * (N_WO / N_AUX)) * OWN_COLS + lane;
            uint32_t dst = sb + SM_FIN + ((lane & 15) * FIN_STRIDE + 8 + fw * 2 + (lane >> 4)) * 4;
            uint32_t t_x5 = prm.t_last + X5_LAG;
            asm volatile("" : "+r"(dst), "+l"(p), "+r"(t_x5));
            mbar_wait(bar_q + X5_PIECE * 8, 1);
            wait_until(t_first[0] - t_first[-1], t_x5);
            unsigned n = 0;
#pragma unroll 1
            while (true) {
                uint32_t w[8];
#pragma unroll
                for (int i = 0; i < 8; i++) w[i] = ll_ld(p + i * 32);
                uint32_t bad[4];
#pragma unroll
                for (int i = 0; i < 4; i++)
                    asm("lop3.b32 %0, %1, %2, %3, 0x7E;" : "=r"(bad[i]) : "r"(w[2 * i]), "r"(w[2 * i + 1]), "r"(tag));
                const float c = ((ll_val(w[0]) + ll_val(w[1])) + (ll_val(w[2]) + ll_val(w[3]))) +
                                ((ll_val(w[4]) + ll_val(w[5])) + (ll_val(w[6]) + ll_val(w[7])));
                sts32(dst, c);
                if (__all_sync(0xffffffffu, !(((bad[0] | bad[1]) | (bad[2] | bad[3])) & 1u)) || ++n > SPIN_LIMIT) break;
            }
            named_arrive(14, N_AUX * 32 + 32);
        }
        return;
    }

    float* sml = reinterpret_cast<float*>(sp + SM_ML);
    if (warp < 5) {
        const uint2 u = xin;
        float s1 = (bf_lo(u.x) + bf_hi(u.x)) + (bf_lo(u.y) + bf_hi(u.y));
#pragma unroll
        for (int o = 16; o > 0; o >>= 1) s1 += __shfl_xor_sync(0xffffffffu, s1, o);
        if (lane == 0) sml[warp] = s1;
        named_sync(10, 160);
        const float mean = (((sml[0] + sml[1]) + (sml[2] + sml[3])) + sml[4]) * (1.f / D_MODEL);
        const float a = bf_lo(u.x) - mean, b = bf_hi(u.x) - mean, c = bf_lo(u.y) - mean, d = bf_hi(u.y) - mean;
        float s2 = fmaf(a, a, fmaf(b, b, fmaf(c, c, d * d)));
#pragma unroll
        for (int o = 16; o > 0; o >>= 1) s2 += __shfl_xor_sync(0xffffffffu, s2, o);
        if (lane == 0) sml[8 + warp] = s2;
        named_sync(10, 160);
        const float var = (((sml[8] + sml[9]) + (sml[10] + sml[11])) + sml[12]) * (1.f / D_MODEL);
        const float mean_b = bf16r(mean);
        float den;
        asm("sqrt.approx.f32 %0, %1;" : "=f"(den) : "f"(bf16r(bf16r(var) + 1e-5f)));
        const float inv = rcp(bf16r(den));
        const uint32_t d0 = pack_bf16(bf_lo(u.x) - mean_b, bf_hi(u.x) - mean_b);
        const uint32_t d1 = pack_bf16(bf_lo(u.y) - mean_b, bf_hi(u.y) - mean_b);
        *reinterpret_cast<uint2*>(sp + SM_XN + tid * 8) =
            make_uint2(pack_bf16(bf_lo(d0) * inv, bf_hi(d0) * inv), pack_bf16(bf_lo(d1) * inv, bf_hi(d1) * inv));
    }
    named_sync(6, N_THREADS);
    const uint32_t tag = (*s_epoch + 1u) & 1u;
    if (tid < Q_PER_CTA) ll_store(g_xq + cta * Q_PER_CTA + tid, tag ^ 1u);

    const int q4 = lane & 3, g8 = lane >> 2;
    const int rowT = (lane & 7) + ((lane >> 4) << 3), hiT = (lane >> 3) & 1;

    uint32_t* x1 = g_x1 + cta * X1_STRIDE + q4 * 8 + g8;
    if (warp < 6) {
        const uint32_t xn_addr = sb + SM_XN + (r * ROWS_PER_CTA + 2 * q4) * 2;
        const int line = 3 * rowT + (warp >> 1);
        const uint32_t o0 = (line * 128 + ((hiT ^ (line & 7)) << 4)) ^ ((warp & 1) << 6), o1 = o0 ^ 32;
        float acc[2][4] = {};
#pragma unroll 1
        for (int t = 0; t < 5; t++) {
            mbar_wait(bar_full + t * 8, 0);
            const uint32_t tb = sb + SM_RING + t * TILE_BYTES;
#pragma unroll
            for (int kk = 0; kk < 2; kk++) {
                const uint32_t b0 = lds32(xn_addr + (t * 32 + kk * 16) * 2);
                const uint32_t b1 = lds32(xn_addr + (t * 32 + kk * 16 + 8) * 2);
                uint32_t a[4];
                ldsm_x4_t(a, tb + kk * 6144 + o0);
                mma_bf16(acc[0], a, b0, b1);
                ldsm_x4_t(a, tb + kk * 6144 + o1);
                mma_bf16(acc[1], a, b0, b1);
            }
        }
        ll_store(x1 + warp * 32, ll_pack(pick4(acc[0][0], acc[0][2], acc[1][0], acc[1][2], q4), tag));
        mbar_wait(bar_full + T_W3 * 8, 0);
        named_sync(11, 192);
        if (tid < 5 * V_WARPS) mbar_arrive(bar_empty + (tid / V_WARPS) * 8);
        if (tid < Q_PER_CTA) {
            const float qv = ll_poll_sum<4>(g_x1 + head * SPLIT * X1_STRIDE + r * Q_PER_CTA + tid, X1_STRIDE, tag);
            ll_store(g_xq + cta * Q_PER_CTA + tid, __float_as_uint(bf16r(qv)) | tag);
        }
        __syncwarp();
        if (tid == 0) mbar_arrive(go_q);
    } else {
        float acc[12][4] = {};
        mbar_wait(bar_full + (T_W1 + warp - 6) * 8, 0);
        const uint32_t xf_addr = sb + SM_XN + ((cta % FF_GROUP) * FF_ROWS + 2 * q4) * 2;
        uint32_t ad[3];
#pragma unroll
        for (int j = 0; j < 3; j++)
            ad[j] = sb + SM_RING + T_W1 * TILE_BYTES + (warp - 6) * W13_BYTES + (3 * rowT + j) * 128 + ((hiT ^ ((3 * rowT + j) & 7)) << 4);
#pragma unroll 1
        for (int ks = 0; ks < 3; ks++) {
            const uint32_t b0 = lds32(xf_addr + ks * 32);
            uint32_t b1 = 0u, step = ks * 6144;
            if (ks < 2) b1 = lds32(xf_addr + ks * 32 + 16);
            else if (lane >= 16) step -= 8 * 384;
#pragma unroll
            for (int mt = 0; mt < 12; mt++) {
                uint32_t a[4];
                ldsm_x4_t(a, (ad[mt >> 2] + step) ^ ((mt & 3) << 5));
                mma_bf16(acc[mt], a, b0, b1);
            }
        }
#pragma unroll
        for (int i = 0; i < 6; i++)
            ll_store(x1 + 192 + (warp - 6) * 192 + i * 32,
                     ll_pack(pick4(acc[2 * i][0], acc[2 * i][2], acc[2 * i + 1][0], acc[2 * i + 1][2], q4), tag));
        named_sync(7, 64);
        if (tid >= 192 && tid < 192 + 3 * V_WARPS) mbar_arrive(bar_empty + (T_W1 + (tid - 192) / V_WARPS) * 8);
    }
    named_sync(1, N_CONS);

    {
        const int rowN = (lane & 7) + (((lane >> 3) & 1) << 3), hiN = lane >> 4;
#pragma unroll 1
        for (int h = warp; h < N_HEAD; h += N_CONS_WARPS) {
            const int t = T_K + h, slot = t & (N_SLOT - 1);
            mbar_wait(bar_q + h * 8, 0);
            mbar_wait(bar_full + slot * 8, (t >> 4) & 1);
            const uint32_t tb = sb + SM_RING + slot * TILE_BYTES;
            const int swz = h < N_PLAIN ? 0 : 7;
            float acc[2][2][4] = {};
#pragma unroll 1
            for (int j = 0; j < 3; j++) {
                const uint32_t oj = tb + (3 * rowN + j) * 128 + ((hiN ^ ((3 * rowN + j) & swz)) << 4);
                const uint32_t qa = sb + SM_Q + h * 384 + (j * 64 + 2 * q4) * 2;
#pragma unroll
                for (int k = 0; k < 4; k++) {
                    const uint32_t b0 = lds32(qa + k * 32), b1 = lds32(qa + k * 32 + 16);
                    uint32_t a[4];
                    ldsm_x4(a, oj ^ (k << 5));
                    mma_bf16(acc[0][k & 1], a, b0, b1);
                    ldsm_x4(a, (oj + 6144) ^ (k << 5));
                    mma_bf16(acc[1][k & 1], a, b0, b1);
                }
            }
            __syncwarp();
            if (lane < V_WARPS) mbar_arrive(bar_empty + slot * 8);
            const float raw = pick4(acc[0][0][0] + acc[0][1][0], acc[0][0][2] + acc[0][1][2],
                                    acc[1][0][0] + acc[1][1][0], acc[1][0][2] + acc[1][1][2], q4);
            const float sc = bf16r(bf16r(raw) * 0.07216878364870323f);
            float mw = sc;
#pragma unroll
            for (int o = 16; o > 0; o >>= 1) mw = fmaxf(mw, __shfl_xor_sync(0xffffffffu, mw, o));
            const float p = ex2((sc - mw) * LOG2E);
            reinterpret_cast<uint16_t*>(sp + SM_P)[h * 32 + q4 * 8 + g8] = (uint16_t)pack_bf16(p, 0.f);
            float lw = p;
#pragma unroll
            for (int o = 16; o > 0; o >>= 1) lw += __shfl_xor_sync(0xffffffffu, lw, o);
            if (lane < X2_STRIDE) ll_store(g_x2 + (h * N_CTA + cta) * X2_STRIDE + lane, ll_pack(lane == 0 ? mw : lw, tag));
            if (lane == 0) {
                reinterpret_cast<float*>(sp + SM_M)[h] = mw;
                if (h == head + S_DELAY) mbar_arrive(go_s);
                if (h >= 23 && (h & 7) == 7) mbar_arrive(go_b + ((h >> 3) - 2) * 8);
            }
        }
    }
    if (odd && q4 < 2) {
#pragma unroll
        for (int j = 0; j < 5; j++) ll_store(g_x5 + ((j * 8 + warp) * N_WO + idx) * OWN_COLS + q4 * 8 + g8, tag ^ 1u);
    }
    named_sync(1, N_CONS);
    if (tid == 0) mbar_arrive(go_k);

    if (warp < V_WARPS) {
        const int line = 3 * rowT + (warp >> 1);
        const uint32_t o0 = (line * 128 + ((hiT ^ (line & 7)) << 4)) ^ ((warp & 1) << 6), o1 = o0 ^ 32;
        uint32_t* x3 = g_x3 + ((warp * 4 + q4) * N_CTA + cta) * 8 + g8;
#pragma unroll
        for (int h = N_HEAD - O_RACING; h < N_HEAD; h++) ll_store(x3 + h * X3_HEAD, tag ^ 1u);
        int s_next = 0, h_next = ((odd ? GROUP0 : 0) + idx) / 24 + O_DELAY;
#pragma unroll 1
        for (int h = 0; h < N_HEAD; h++) {
            const int slot = (T_V + h) & (N_SLOT - 1);
            if ((h & 7) == 0) mbar_wait(bar_s + h, 0);
            const float2 ms = *reinterpret_cast<const float2*>(sp + SM_S + h * 8);
            const float scale = ex2((reinterpret_cast<const float*>(sp + SM_M)[h] - ms.x) * LOG2E) * ms.y;
            mbar_wait(bar_full + slot * 8, ((T_V + h) >> 4) & 1);
            const uint32_t tb = sb + SM_RING + slot * TILE_BYTES;
            const uint32_t pa = sb + SM_P + (h * 32 + 2 * q4) * 2;
            float oacc[2][2][4] = {};
#pragma unroll
            for (int kk = 0; kk < 2; kk++) {
                const uint32_t b0 = lds32(pa + kk * 32), b1 = lds32(pa + kk * 32 + 16);
                uint32_t a[4];
                ldsm_x4_t(a, tb + kk * 6144 + o0);
                mma_bf16(oacc[0][kk], a, b0, b1);
                ldsm_x4_t(a, tb + kk * 6144 + o1);
                mma_bf16(oacc[1][kk], a, b0, b1);
            }
            __syncwarp();
            if (lane == 0) mbar_arrive(bar_empty + slot * 8);
            const float v = pick4(oacc[0][0][0] + oacc[0][1][0], oacc[0][0][2] + oacc[0][1][2],
                                  oacc[1][0][0] + oacc[1][1][0], oacc[1][0][2] + oacc[1][1][2], q4);
            ll_store(x3 + h * X3_HEAD, ll_pack(v * scale, tag));
            if (tid == 0) {
                if (h == head + S_DELAY - N_HEAD) mbar_arrive(go_s);
                if (h == 7 || h == 21) mbar_arrive(go_b + (h == 7 ? 2 : 3) * 8);
                while (h == h_next) {
                    mbar_arrive(go_o + s_next * 8);
                    s_next++;
                    if (odd) h_next = s_next < WO_ROUNDS ? min((GROUP0 + s_next * N_WO + idx) / 24 + O_DELAY, N_HEAD - 1) : -1;
                    else h_next = s_next < XO_GROUPS ? (s_next * N_WO + idx) / 24 + O_DELAY : s_next == XO_GROUPS ? XO_TILE : -1;
                }
            }
        }
    }

    constexpr int STEPS = N_PIECE / N_CONS_WARPS, W2_STEPS = W2_PIECES / N_CONS_WARPS;
    uint32_t hb[STEPS][4][2];
    if (owner) {
        named_sync(4, N_AUX * 32 + N_CONS);
#pragma unroll
        for (int k = 0; k < STEPS; k++)
#pragma unroll
            for (int i = 0; i < 4; i++) {
                const uint32_t ha = sb + SM_H + ((k * N_CONS_WARPS + warp) * PIECE_ROWS + i * 16 + 2 * q4) * 2;
                hb[k][i][0] = lds32(ha);
                hb[k][i][1] = lds32(ha + 16);
            }
    }

    if (odd) {
        uint32_t* x5 = g_x5 + (warp * N_WO + idx) * OWN_COLS + (q4 & 1) * 8 + g8;
        asm volatile("" : "+l"(x5));
        named_sync(3, N_CONS + N_AUX * 32);
        float acc[5][4] = {};
        uint32_t wa = sb + SM_RING + TAIL_SLOT * TILE_BYTES + (lane >> 4) * 2048 + (warp >> 2) * 1024 + (lane & 7) * 128 +
                      (((((warp & 3) << 1) | hiT) ^ (lane & 7)) << 4);
        auto multiply = [&](int p) {
            const uint32_t b0 = lds32(sb + SM_O + (p * 8 + 2 * q4) * 2);
            mbar_wait(bar_t + p * 8, 0);
            uint32_t a0[4], a1[4], a2[2];
            ldsm_x4_t(a0, wa);
            ldsm_x4_t(a1, wa + 4096);
            ldsm_x2_t(a2, wa + 8192);
            mma_bf16_k8(acc[0], a0[0], a0[1], b0);
            mma_bf16_k8(acc[1], a0[2], a0[3], b0);
            mma_bf16_k8(acc[2], a1[0], a1[1], b0);
            mma_bf16_k8(acc[3], a1[2], a1[3], b0);
            mma_bf16_k8(acc[4], a2[0], a2[1], b0);
        };
#pragma unroll 1
        for (int p = 0; p < WO_ROUNDS - 1; p++) {
            if (p == 2 * N_AUX) named_sync(13, N_CONS + N_AUX * 32);
            multiply(p);
            wa += p == WO_WRAP - 1 ? -(TAIL_SLOT * TILE_BYTES + (WO_WRAP - 1) * WO_BYTES) : WO_BYTES;
        }
        multiply(WO_ROUNDS - 1);
#pragma unroll
        for (int j = 0; j < 5; j++) ll_store(x5 + j * 8 * N_WO * OWN_COLS, ll_pack(q4 & 1 ? acc[j][2] : acc[j][0], tag));
    }

    if (owner) {
        float acc[4][4] = {};
        const uint32_t wa = sb + SM_RING + TAIL_SLOT * TILE_BYTES + (warp * PIECE_ROWS + rowT) * 32 + ((hiT ^ ((lane >> 2) & 1)) << 4);
        uint32_t fin_f = sb + SM_FIN + (16 * FIN_STRIDE + warp * 16 + (q4 & 1) * 8 + g8) * 4;
        uint32_t fin_s = sb + SM_FIN + (((q4 & 1) * 8 + g8) * FIN_STRIDE + warp) * 4;
        uint32_t bar = bar_q + warp * 8;
        asm volatile("" : "+r"(fin_f), "+r"(fin_s), "+r"(bar));
#pragma unroll
        for (int k = 0; k < STEPS; k++) {
            if (k < N_HEAD / N_CONS_WARPS) mbar_wait(bar + k * N_CONS_WARPS * 8, 1);
            else mbar_wait(bar - (bar_q - bar_t), 0);
            uint32_t a[4][4];
#pragma unroll
            for (int i = 0; i < 4; i++) ldsm_x4_t(a[i], wa + k * N_CONS_WARPS * PIECE_BYTES + i * 512);
#pragma unroll
            for (int i = 0; i < 4; i++) mma_bf16(acc[i], a[i], hb[k][i][0], hb[k][i][1]);
            if (k == W2_STEPS - 1 || k == STEPS - 1) {
                const float part = q4 ? (acc[0][2] + acc[1][2]) + (acc[2][2] + acc[3][2]) : (acc[0][0] + acc[1][0]) + (acc[2][0] + acc[3][0]);
                if (q4 < 2) sts32(k < W2_STEPS ? fin_f : fin_s, part);
                named_arrive(k < W2_STEPS ? 5 : 12, N_CONS + 32);
#pragma unroll
                for (int i = 0; i < 4; i++) acc[0][i] = acc[1][i] = acc[2][i] = acc[3][i] = 0.f;
            }
        }
    }
    return;
}


typedef CUresult (*EncodeTiledFn)(CUtensorMap*, CUtensorMapDataType, cuuint32_t, void*, const cuuint64_t*,
                                  const cuuint64_t*, const cuuint32_t*, const cuuint32_t*, CUtensorMapInterleave,
                                  CUtensorMapSwizzle, CUtensorMapL2promotion, CUtensorMapFloatOOBfill);

void encode_map(EncodeTiledFn fn, CUtensorMap* m, const void* base, cuuint64_t d1, cuuint64_t d2, cuuint64_t s1,
                cuuint64_t s2, cuuint32_t b1, cuuint32_t b2) {
    const cuuint64_t dims[3] = {64, d1, d2};
    const cuuint64_t strides[2] = {s1, s2};
    const cuuint32_t box[3] = {64, b1, b2};
    const cuuint32_t estr[3] = {1, 1, 1};
    fn(m, CU_TENSOR_MAP_DATA_TYPE_BFLOAT16, 3, const_cast<void*>(base), dims, strides, box, estr,
       CU_TENSOR_MAP_INTERLEAVE_NONE, CU_TENSOR_MAP_SWIZZLE_128B, CU_TENSOR_MAP_L2_PROMOTION_NONE,
       CU_TENSOR_MAP_FLOAT_OOB_FILL_NONE);
}

}

extern "C" void kernel_launch(void* const* d_in, const int* in_sizes, int n_in, void* d_out, int out_size) {
    (void)in_sizes; (void)n_in; (void)out_size;
    static EncodeTiledFn encode = nullptr;
    static double pace_scale = 1.0;
    if (!encode) {
        int dev = 0, mem_khz = 0, bus_bits = 0;
        cudaGetDevice(&dev);
        cudaDeviceGetAttribute(&mem_khz, cudaDevAttrMemoryClockRate, dev);
        cudaDeviceGetAttribute(&bus_bits, cudaDevAttrGlobalMemoryBusWidth, dev);
        const double peak_gbs = 2.0 * mem_khz * 1e-6 * bus_bits / 8.0;
        if (peak_gbs > 0.0) pace_scale = PACE_REF_GBS / peak_gbs;
        void* fn = nullptr;
        cudaDriverEntryPointQueryResult qr;
        cudaGetDriverEntryPoint("cuTensorMapEncodeTiled", &fn, cudaEnableDefault, &qr);
        encode = reinterpret_cast<EncodeTiledFn>(fn);
        cudaFuncSetAttribute(fused_decode_kernel, cudaFuncAttributeMaxDynamicSharedMemorySize, SM_ALLOC);
    }
    CUtensorMap tm_k, tm_v, tm_wq, tm_w1, tm_w3, tm_wo, tm_w2, tm_wc;
    {
        const cuuint64_t dims[3] = {D_MODEL, D_FF, 1};
        const cuuint64_t strides[2] = {D_MODEL * 2, (cuuint64_t)D_MODEL * 2 * D_FF};
        const cuuint32_t box[3] = {OWN_COLS, PIECE_ROWS, 1};
        const cuuint32_t estr[3] = {1, 1, 1};
        encode(&tm_w2, CU_TENSOR_MAP_DATA_TYPE_BFLOAT16, 3, d_in[8], dims, strides, box, estr, CU_TENSOR_MAP_INTERLEAVE_NONE,
               CU_TENSOR_MAP_SWIZZLE_32B, CU_TENSOR_MAP_L2_PROMOTION_NONE, CU_TENSOR_MAP_FLOAT_OOB_FILL_NONE);
        encode(&tm_wc, CU_TENSOR_MAP_DATA_TYPE_BFLOAT16, 3, d_in[4], dims, strides, box, estr, CU_TENSOR_MAP_INTERLEAVE_NONE,
               CU_TENSOR_MAP_SWIZZLE_32B, CU_TENSOR_MAP_L2_PROMOTION_NONE, CU_TENSOR_MAP_FLOAT_OOB_FILL_NONE);
    }
    encode_map(encode, &tm_k, d_in[1], 3, (cuuint64_t)N_HEAD * SEQ, 128, D_HEAD * 2, 3, SUB_ROWS);
    encode_map(encode, &tm_v, d_in[2], 3, (cuuint64_t)N_HEAD * SEQ, 128, D_HEAD * 2, 3, SUB_ROWS);
    encode_map(encode, &tm_wq, d_in[3], N_HEAD * 3, D_MODEL, 128, N_HEAD * D_HEAD * 2, 3, SUB_ROWS);
    encode_map(encode, &tm_w1, d_in[6], D_FF / 64, D_MODEL, 128, D_FF * 2, 3, 8);
    encode_map(encode, &tm_w3, d_in[7], D_FF / 64, D_MODEL, 128, D_FF * 2, 3, 8);
    encode_map(encode, &tm_wo, d_in[4], N_HEAD * D_HEAD, D_MODEL / 64, D_MODEL * 2, 128, 8, 10);
    Params prm;
    prm.x = static_cast<const __nv_bfloat16*>(d_in[0]);
    prm.k_win = static_cast<const __nv_bfloat16*>(d_in[1]) + (size_t)(SEQ - WIN) * D_HEAD;
    prm.out = static_cast<__nv_bfloat16*>(d_out);
    auto step = [&](double pace, double bytes) { return (uint32_t)(pace * pace_scale * bytes / TILE_BYTES + 0.01); };
    prm.step = step(PACE, SUB_ROWS * 384);
    prm.step_ffn = step(PACE, 8 * 384);
    prm.step_wo = step(PACE_WO, WO_BYTES / 2);
    prm.step_start = (uint32_t)(PACE_START * pace_scale + 0.5);
    prm.step_ahead = step(PACE_AHEAD, AHEAD_ROWS * D_MODEL);
    const uint32_t t_k = prm.step_start + 2 * T_W1 * prm.step + 2 * (FF_ROWS / 8) * prm.step_ffn;
    prm.t_late = t_k + (2 * (LATE_TILE - T_K - N_PLAIN) + 1) * prm.step + LATE_NS;
    prm.t_last = t_k + 2 * (T_END - T_K - N_PLAIN) * prm.step + (WO_ROUNDS - 1) * prm.step_wo;
    prm.w2 = static_cast<const char*>(d_in[8]);
    prm.wo = static_cast<const char*>(d_in[4]);
    fused_decode_kernel<<<N_CTA, N_THREADS, SM_ALLOC, cudaStreamPerThread>>>(
        prm, tm_wq, tm_w1, tm_w3, tm_k, tm_v, tm_wo, tm_w2, tm_wc);
}
```
